```python
import torch

def _softmax(x, axis=-1):
    return torch.softmax(x, dim=axis)
def _gelu(x):
    return torch.nn.functional.gelu(x, approximate="tanh")
def _silu(x):
    return torch.nn.functional.silu(x)
def _sigmoid(x):
    return torch.sigmoid(x)
def _layernorm(x, axis=-1, eps=1e-5):
    m = x.mean(dim=axis, keepdim=True)
    v = x.var(dim=axis, keepdim=True, unbiased=False)
    return (x - m) / torch.sqrt(v + eps)
def _scatter_add(tgt, idx, src, axis=0):
    return tgt.clone().index_add_(axis, idx, src)
def _segment_sum(src, seg, n):
    out = torch.zeros((n,) + src.shape[1:], dtype=src.dtype)
    return out.index_add_(0, seg, src)
def _pad(x, pw):
    flat = tuple(v for pair in reversed(pw) for v in pair)
    return torch.nn.functional.pad(x, flat)

kernel_name = 'recurrent_scan__linear_kernel_hedgehog__mixer_token_mlp__prompt'

def setup_inputs():

    _w = (lambda a: (lambda t: t.to(torch.bfloat16) if t.is_floating_point() else t)(torch.as_tensor(a)))
    def _A_setup():
        B, S, D, H = 1, 2048, 576, 32
        Dh = D // H
        return {
            "x": _w((lambda *s: torch.randn(*s, dtype=torch.bfloat16) * 0.05)(B, S, D)),
            "wqkv": _w((lambda *s: torch.randn(*s, dtype=torch.bfloat16) * 0.4)(D, 3 * D)),
            "w_phi": _w((lambda *s: torch.randn(*s, dtype=torch.bfloat16) * 0.4)(H, Dh, Dh) * (Dh ** -0.5)),
            "wo": _w((lambda *s: torch.randn(*s, dtype=torch.bfloat16) * 0.2)(D, D)),
        }
    _A_in = _A_setup()

    def _B_setup():
        B, S, D, F = 1, 2048, 576, 4608
        return {
            "x": _w((lambda *s: torch.randn(*s, dtype=torch.bfloat16) * 0.05)(B, S, D)),
            "w1": _w((lambda *s: torch.randn(*s, dtype=torch.bfloat16) * 0.4)(S, F) * (S ** -0.5)),
            "b1": _w((lambda *s: torch.randn(*s, dtype=torch.bfloat16) * 3.2)(F) * 0.02),
            "w2": _w((lambda *s: torch.randn(*s, dtype=torch.bfloat16) * 0.1)(F, S) * (F ** -0.5)),
            "b2": _w((lambda *s: torch.randn(*s, dtype=torch.bfloat16) * 0.2)(S) * 0.02),
        }
    _B_in = _B_setup()

    return {
        "A_x": _A_in["x"],
        "A_wqkv": _A_in["wqkv"],
        "A_w_phi": _A_in["w_phi"],
        "A_wo": _A_in["wo"],
        "B_x": _B_in["x"],
        "B_w1": _B_in["w1"],
        "B_b1": _B_in["b1"],
        "B_w2": _B_in["w2"],
        "B_b2": _B_in["b2"],
    }

def reference(A_x, A_wqkv, A_w_phi, A_wo, B_x, B_w1, B_b1, B_w2, B_b2):
    def _A_ref(x, wqkv, w_phi, wo):
        B, S, D = x.shape
        H = 32; Dh = D // H
        qkv = (lambda x, *d: x.permute(*d))((x @ wqkv).reshape(B, S, 3, H, Dh), 2, 0, 3, 1, 4)
        q, k, v = qkv[0], qkv[1], qkv[2]
        pq = torch.einsum("bhsd,hdf->bhsf", q, w_phi)
        pk = torch.einsum("bhsd,hdf->bhsf", k, w_phi)
        phi_q = torch.concatenate([_softmax(pq, axis=-1), _softmax(-pq, axis=-1)], axis=-1)
        phi_k = torch.concatenate([_softmax(pk, axis=-1), _softmax(-pk, axis=-1)], axis=-1)
        kv = torch.einsum("bhsf,bhsd->bhfd", phi_k, v)
        z  = torch.einsum("bhsf->bhf", phi_k)
        num = torch.einsum("bhqf,bhfd->bhqd", phi_q, kv)
        den = torch.einsum("bhqf,bhf->bhq", phi_q, z)[..., None] + 1e-6
        o = num / den
        return (lambda x, *d: x.permute(*d))(o, 0, 2, 1, 3).reshape(B, S, D) @ wo

    def _B_ref(x, w1, b1, w2, b2):
        B, S, D = x.shape
        h = _layernorm(x, axis=-1)
        u = torch.einsum("bsd,sf->bdf", h, w1) + b1
        u = _gelu(u)
        y = torch.einsum("bdf,fs->bds", u, w2) + b2
        return (lambda x, *d: x.permute(*d))(y, 0, 2, 1)

    x = A_x
    xn = _layernorm(x, axis=-1)
    s = _A_ref(xn, A_wqkv, A_w_phi, A_wo)
    g = _silu(_B_ref(xn, B_w1, B_b1, B_w2, B_b2))
    return x + s * g
```

```cpp
#include <cuda_runtime.h>
#include <cuda_bf16.h>
#include <cuda.h>
#include <stdint.h>

namespace {

typedef __nv_bfloat16 bf16;
constexpr int S_ = 2048, D_ = 576, F_ = 4608;
constexpr int NCTA = 132;
constexpr int NATT = 36;
constexpr int MAXITEMS = 10;

constexpr int MLP_STAGE = 40960;
constexpr int ATT_STAGE = 34816;
constexpr int OFF_USTG = 4 * MLP_STAGE;
constexpr int OFF_ATT = 4 * ATT_STAGE;
constexpr int PH_HS = 5152, V_HS = 3104;
constexpr int A1_STG = 4 * PH_HS + 4 * V_HS;
constexpr int KVB_BYTES = 23040;
constexpr int OFF_OSTG = OFF_ATT + 2 * KVB_BYTES;
constexpr int OFF_BAR = 222208;
constexpr int SMEM_BYTES = OFF_BAR + 256 + 1024;
constexpr int B_FULL = 0, B_EMPTY = 32, B_XCH = 64, B_XRDY = 96, B_KVB = 104;

__device__ __align__(1024) bf16 g_xn[S_ * D_];
__device__ __align__(1024) bf16 g_h[S_ * D_];
__device__ __align__(1024) bf16 g_u[F_ * D_];
__device__ __align__(1024) bf16 g_o[S_ * D_];
__device__ __align__(1024) bf16 g_wtkv[8 * 144 * D_];
__device__ __align__(1024) bf16 g_wtq[8 * 72 * D_];
__device__ __align__(1024) float g_kv[32 * 36 * 20];
__device__ __align__(1024) unsigned g_cnt[32 * 32];
__device__ unsigned g_abort;
constexpr int C_LN = 0, C_PREP = 1, C_KV = 2, C_DONE = 3, C_U = 4, C_O = 10, C_NUM = 26;
#define PROF(i) do {} while (0)
#define PROF1(i) do {} while (0)

struct Params {
  CUtensorMap w1, h, w2, u, xn, wkv, wq, o_st, o_ld, wo, x, out;
  const bf16 *xp, *wqkv, *wphi, *b1, *b2;
  uint8_t role[66];
  uint8_t nitems[NATT];
  uint8_t items[NATT][MAXITEMS];
};

__device__ __forceinline__ uint32_t smem_u32(const void* p) { return (uint32_t)__cvta_generic_to_shared(p); }
__device__ __forceinline__ void mbar_init(uint32_t bar, uint32_t cnt) { asm volatile("mbarrier.init.shared::cta.b64 [%0], %1;" :: "r"(bar), "r"(cnt) : "memory"); }
__device__ __forceinline__ void mbar_expect_tx(uint32_t bar, uint32_t bytes) { asm volatile("mbarrier.arrive.expect_tx.shared::cta.b64 _, [%0], %1;" :: "r"(bar), "r"(bytes) : "memory"); }
__device__ __forceinline__ void mbar_arrive(uint32_t bar) { asm volatile("mbarrier.arrive.shared::cta.b64 _, [%0];" :: "r"(bar) : "memory"); }
__device__ __forceinline__ uint32_t mapa(uint32_t addr, uint32_t rank) { uint32_t r; asm volatile("mapa.shared::cluster.u32 %0, %1, %2;" : "=r"(r) : "r"(addr), "r"(rank)); return r; }
__device__ __forceinline__ void mbar_arrive_remote(uint32_t raddr) { asm volatile("mbarrier.arrive.release.cluster.shared::cluster.b64 _, [%0];" :: "r"(raddr) : "memory"); }
__device__ __forceinline__ bool mbar_try_wait(uint32_t bar, uint32_t parity) {
  uint32_t ok;
  asm volatile("{\n.reg .pred p;\nmbarrier.try_wait.parity.shared::cta.b64 p, [%1], %2;\nselp.u32 %0, 1, 0, p;\n}" : "=r"(ok) : "r"(bar), "r"(parity) : "memory");
  return ok;
}
__device__ __forceinline__ bool bail(uint32_t& n) {
  if ((++n & 0x3FFu) == 0) {
    if (n >= (1u << 22)) *(volatile unsigned*)&g_abort = 1u;
    if (*(volatile unsigned*)&g_abort) return true;
  }
  return false;
}
__device__ __forceinline__ void mbar_wait(uint32_t bar, uint32_t parity) {
  uint32_t n = 0;
  while (!mbar_try_wait(bar, parity)) { if (bail(n)) break; }
}
__device__ __forceinline__ void mbar_wait_cluster(uint32_t bar, uint32_t parity) {
  uint32_t n = 0, ok;
  do {
    asm volatile("{\n.reg .pred p;\nmbarrier.try_wait.parity.acquire.cluster.shared::cta.b64 p, [%1], %2;\nselp.u32 %0, 1, 0, p;\n}" : "=r"(ok) : "r"(bar), "r"(parity) : "memory");
    if (!ok && bail(n)) break;
  } while (!ok);
}
__device__ __forceinline__ void tma_2d(uint32_t dst, const CUtensorMap* map, uint32_t bar, int c0, int c1) {
  asm volatile("cp.async.bulk.tensor.2d.shared::cluster.global.mbarrier::complete_tx::bytes [%0], [%1, {%3, %4}], [%2];"
    :: "r"(dst), "l"(map), "r"(bar), "r"(c0), "r"(c1) : "memory");
}
__device__ __forceinline__ void tma_3d(uint32_t dst, const CUtensorMap* map, uint32_t bar, int c0, int c1, int c2) {
  asm volatile("cp.async.bulk.tensor.3d.shared::cluster.global.mbarrier::complete_tx::bytes [%0], [%1, {%3, %4, %5}], [%2];"
    :: "r"(dst), "l"(map), "r"(bar), "r"(c0), "r"(c1), "r"(c2) : "memory");
}
__device__ __forceinline__ void tma_st_2d(const CUtensorMap* map, uint32_t src, int c0, int c1) {
  asm volatile("cp.async.bulk.tensor.2d.global.shared::cta.bulk_group [%0, {%2, %3}], [%1];" :: "l"(map), "r"(src), "r"(c0), "r"(c1) : "memory");
}
__device__ __forceinline__ void tma_st_3d(const CUtensorMap* map, uint32_t src, int c0, int c1, int c2) {
  asm volatile("cp.async.bulk.tensor.3d.global.shared::cta.bulk_group [%0, {%2, %3, %4}], [%1];" :: "l"(map), "r"(src), "r"(c0), "r"(c1), "r"(c2) : "memory");
}
__device__ __forceinline__ void bulk_commit() { asm volatile("cp.async.bulk.commit_group;" ::: "memory"); }
__device__ __forceinline__ void bulk_wait0() { asm volatile("cp.async.bulk.wait_group 0;" ::: "memory"); }
__device__ __forceinline__ void bulk_wait0_read() { asm volatile("cp.async.bulk.wait_group.read 0;" ::: "memory"); }
__device__ __forceinline__ void prefetch_map(const CUtensorMap* map) { asm volatile("prefetch.tensormap [%0];" :: "l"(map) : "memory"); }
__device__ __forceinline__ void fence_async_smem() { asm volatile("fence.proxy.async.shared::cta;" ::: "memory"); }
__device__ __forceinline__ void fence_async_all() { asm volatile("fence.proxy.async;" ::: "memory"); }
__device__ __forceinline__ void wgmma_fence() { asm volatile("wgmma.fence.sync.aligned;" ::: "memory"); }
__device__ __forceinline__ void wgmma_commit() { asm volatile("wgmma.commit_group.sync.aligned;" ::: "memory"); }
template <int N> __device__ __forceinline__ void wgmma_wait() { asm volatile("wgmma.wait_group.sync.aligned %0;" :: "n"(N) : "memory"); }
__device__ __forceinline__ void bar_sync(int id, int n) { asm volatile("bar.sync %0, %1;" :: "r"(id), "r"(n) : "memory"); }
__device__ __forceinline__ void bar_arrive(int id, int n) { asm volatile("bar.arrive %0, %1;" :: "r"(id), "r"(n) : "memory"); }
__device__ __forceinline__ uint64_t make_desc(uint32_t addr, uint32_t lbo, uint32_t sbo, uint32_t swz) {
  return (uint64_t)((addr & 0x3FFFF) >> 4) | ((uint64_t)(lbo >> 4) << 16) | ((uint64_t)(sbo >> 4) << 32) | ((uint64_t)swz << 62);
}
__device__ __forceinline__ void signal(int c, unsigned v = 1) { asm volatile("red.release.gpu.global.add.u32 [%0], %1;" :: "l"(&g_cnt[c * 32]), "r"(v) : "memory"); }
__device__ __forceinline__ void wait_cnt(int c, unsigned target) {
  unsigned v; uint32_t n = 0;
  while (true) {
    asm volatile("ld.acquire.gpu.global.u32 %0, [%1];" : "=r"(v) : "l"(&g_cnt[c * 32]) : "memory");
    if (v >= target) break;
    if (bail(n)) break;
  }
}
__device__ __forceinline__ uint32_t pack2(float lo, float hi) { uint32_t r; asm("cvt.rn.bf16x2.f32 %0, %1, %2;" : "=r"(r) : "f"(hi), "f"(lo)); return r; }
__device__ __forceinline__ float bf_lo(uint32_t v) { return __uint_as_float(v << 16); }
__device__ __forceinline__ float bf_hi(uint32_t v) { return __uint_as_float(v & 0xFFFF0000u); }
__device__ __forceinline__ float rbf(float v) { return __bfloat162float(__float2bfloat16_rn(v)); }
__device__ __forceinline__ float ex2(float x) { float r; asm volatile("ex2.approx.ftz.f32 %0, %1;" : "=f"(r) : "f"(x)); return r; }
__device__ __forceinline__ uint32_t opaque(uint32_t x) { uint32_t r; asm volatile("mov.u32 %0, %1;" : "=r"(r) : "r"(x)); return r; }
__device__ __forceinline__ float tanh_fast(float x) { float r; asm("tanh.approx.f32 %0, %1;" : "=f"(r) : "f"(x)); return r; }
__device__ __forceinline__ float rcp_fast(float x) { float r; asm("rcp.approx.ftz.f32 %0, %1;" : "=f"(r) : "f"(x)); return r; }
__device__ __forceinline__ void stsm4(uint32_t addr, uint32_t r0, uint32_t r1, uint32_t r2, uint32_t r3) {
  asm volatile("stmatrix.sync.aligned.m8n8.x4.shared.b16 [%0], {%1, %2, %3, %4};" :: "r"(addr), "r"(r0), "r"(r1), "r"(r2), "r"(r3) : "memory");
}
__device__ __forceinline__ void ldsm4(uint32_t addr, uint32_t& r0, uint32_t& r1, uint32_t& r2, uint32_t& r3) {
  asm volatile("ldmatrix.sync.aligned.m8n8.x4.shared.b16 {%0, %1, %2, %3}, [%4];" : "=r"(r0), "=r"(r1), "=r"(r2), "=r"(r3) : "r"(addr) : "memory");
}
__device__ __forceinline__ void sts128(uint32_t addr, uint32_t a, uint32_t b, uint32_t c, uint32_t d) {
  asm volatile("st.shared.v4.b32 [%0], {%1, %2, %3, %4};" :: "r"(addr), "r"(a), "r"(b), "r"(c), "r"(d) : "memory");
}
__device__ __forceinline__ void sts64(uint32_t addr, uint32_t a, uint32_t b) { asm volatile("st.shared.v2.b32 [%0], {%1, %2};" :: "r"(addr), "r"(a), "r"(b) : "memory"); }
__device__ __forceinline__ void sts32(uint32_t addr, uint32_t a) { asm volatile("st.shared.b32 [%0], %1;" :: "r"(addr), "r"(a) : "memory"); }
__device__ __forceinline__ void mma16816(float (&d)[4], uint32_t a0, uint32_t a1, uint32_t a2, uint32_t a3, uint32_t b0, uint32_t b1) {
  asm volatile("mma.sync.aligned.m16n8k16.row.col.f32.bf16.bf16.f32 {%0, %1, %2, %3}, {%4, %5, %6, %7}, {%8, %9}, {%0, %1, %2, %3};"
    : "+f"(d[0]), "+f"(d[1]), "+f"(d[2]), "+f"(d[3]) : "r"(a0), "r"(a1), "r"(a2), "r"(a3), "r"(b0), "r"(b1));
}
__device__ __forceinline__ uint32_t ldg32(const void* p) { uint32_t v; asm volatile("ld.global.nc.b32 %0, [%1];" : "=r"(v) : "l"(p)); return v; }
__device__ __forceinline__ uint32_t ldg16(const void* p) { unsigned short v; asm volatile("ld.global.nc.u16 %0, [%1];" : "=h"(v) : "l"(p)); return v; }

__device__ __forceinline__ void wgmma_ss_n192_t11(float (&d)[96], uint64_t da, uint64_t db, int sc) {
  asm volatile("{\n.reg .pred p;\nsetp.ne.b32 p, %98, 0;\n"
    "wgmma.mma_async.sync.aligned.m64n192k16.f32.bf16.bf16 {%0, %1, %2, %3, %4, %5, %6, %7, %8, %9, %10, %11, %12, %13, %14, %15, %16, %17, %18, %19, %20, %21, %22, %23, %24, %25, %26, %27, %28, %29, %30, %31, %32, %33, %34, %35, %36, %37, %38, %39, %40, %41, %42, %43, %44, %45, %46, %47, %48, %49, %50, %51, %52, %53, %54, %55, %56, %57, %58, %59, %60, %61, %62, %63, %64, %65, %66, %67, %68, %69, %70, %71, %72, %73, %74, %75, %76, %77, %78, %79, %80, %81, %82, %83, %84, %85, %86, %87, %88, %89, %90, %91, %92, %93, %94, %95}, %96, %97, p, 1, 1, 1, 1;\n}\n"
    : "+f"(d[0]), "+f"(d[1]), "+f"(d[2]), "+f"(d[3]), "+f"(d[4]), "+f"(d[5]), "+f"(d[6]), "+f"(d[7]), "+f"(d[8]), "+f"(d[9]), "+f"(d[10]), "+f"(d[11]), "+f"(d[12]), "+f"(d[13]), "+f"(d[14]), "+f"(d[15]), "+f"(d[16]), "+f"(d[17]), "+f"(d[18]), "+f"(d[19]), "+f"(d[20]), "+f"(d[21]), "+f"(d[22]), "+f"(d[23]), "+f"(d[24]), "+f"(d[25]), "+f"(d[26]), "+f"(d[27]), "+f"(d[28]), "+f"(d[29]), "+f"(d[30]), "+f"(d[31]), "+f"(d[32]), "+f"(d[33]), "+f"(d[34]), "+f"(d[35]), "+f"(d[36]), "+f"(d[37]), "+f"(d[38]), "+f"(d[39]), "+f"(d[40]), "+f"(d[41]), "+f"(d[42]), "+f"(d[43]), "+f"(d[44]), "+f"(d[45]), "+f"(d[46]), "+f"(d[47]), "+f"(d[48]), "+f"(d[49]), "+f"(d[50]), "+f"(d[51]), "+f"(d[52]), "+f"(d[53]), "+f"(d[54]), "+f"(d[55]), "+f"(d[56]), "+f"(d[57]), "+f"(d[58]), "+f"(d[59]), "+f"(d[60]), "+f"(d[61]), "+f"(d[62]), "+f"(d[63]), "+f"(d[64]), "+f"(d[65]), "+f"(d[66]), "+f"(d[67]), "+f"(d[68]), "+f"(d[69]), "+f"(d[70]), "+f"(d[71]), "+f"(d[72]), "+f"(d[73]), "+f"(d[74]), "+f"(d[75]), "+f"(d[76]), "+f"(d[77]), "+f"(d[78]), "+f"(d[79]), "+f"(d[80]), "+f"(d[81]), "+f"(d[82]), "+f"(d[83]), "+f"(d[84]), "+f"(d[85]), "+f"(d[86]), "+f"(d[87]), "+f"(d[88]), "+f"(d[89]), "+f"(d[90]), "+f"(d[91]), "+f"(d[92]), "+f"(d[93]), "+f"(d[94]), "+f"(d[95])
    : "l"(da), "l"(db), "r"(sc));
}
__device__ __forceinline__ void wgmma_ss_n96_t01(float (&d)[48], uint64_t da, uint64_t db, int sc) {
  asm volatile("{\n.reg .pred p;\nsetp.ne.b32 p, %50, 0;\n"
    "wgmma.mma_async.sync.aligned.m64n96k16.f32.bf16.bf16 {%0, %1, %2, %3, %4, %5, %6, %7, %8, %9, %10, %11, %12, %13, %14, %15, %16, %17, %18, %19, %20, %21, %22, %23, %24, %25, %26, %27, %28, %29, %30, %31, %32, %33, %34, %35, %36, %37, %38, %39, %40, %41, %42, %43, %44, %45, %46, %47}, %48, %49, p, 1, 1, 0, 1;\n}\n"
    : "+f"(d[0]), "+f"(d[1]), "+f"(d[2]), "+f"(d[3]), "+f"(d[4]), "+f"(d[5]), "+f"(d[6]), "+f"(d[7]), "+f"(d[8]), "+f"(d[9]), "+f"(d[10]), "+f"(d[11]), "+f"(d[12]), "+f"(d[13]), "+f"(d[14]), "+f"(d[15]), "+f"(d[16]), "+f"(d[17]), "+f"(d[18]), "+f"(d[19]), "+f"(d[20]), "+f"(d[21]), "+f"(d[22]), "+f"(d[23]), "+f"(d[24]), "+f"(d[25]), "+f"(d[26]), "+f"(d[27]), "+f"(d[28]), "+f"(d[29]), "+f"(d[30]), "+f"(d[31]), "+f"(d[32]), "+f"(d[33]), "+f"(d[34]), "+f"(d[35]), "+f"(d[36]), "+f"(d[37]), "+f"(d[38]), "+f"(d[39]), "+f"(d[40]), "+f"(d[41]), "+f"(d[42]), "+f"(d[43]), "+f"(d[44]), "+f"(d[45]), "+f"(d[46]), "+f"(d[47])
    : "l"(da), "l"(db), "r"(sc));
}
__device__ __forceinline__ void wgmma_ss_n144_t00(float (&d)[72], uint64_t da, uint64_t db, int sc) {
  asm volatile("{\n.reg .pred p;\nsetp.ne.b32 p, %74, 0;\n"
    "wgmma.mma_async.sync.aligned.m64n144k16.f32.bf16.bf16 {%0, %1, %2, %3, %4, %5, %6, %7, %8, %9, %10, %11, %12, %13, %14, %15, %16, %17, %18, %19, %20, %21, %22, %23, %24, %25, %26, %27, %28, %29, %30, %31, %32, %33, %34, %35, %36, %37, %38, %39, %40, %41, %42, %43, %44, %45, %46, %47, %48, %49, %50, %51, %52, %53, %54, %55, %56, %57, %58, %59, %60, %61, %62, %63, %64, %65, %66, %67, %68, %69, %70, %71}, %72, %73, p, 1, 1, 0, 0;\n}\n"
    : "+f"(d[0]), "+f"(d[1]), "+f"(d[2]), "+f"(d[3]), "+f"(d[4]), "+f"(d[5]), "+f"(d[6]), "+f"(d[7]), "+f"(d[8]), "+f"(d[9]), "+f"(d[10]), "+f"(d[11]), "+f"(d[12]), "+f"(d[13]), "+f"(d[14]), "+f"(d[15]), "+f"(d[16]), "+f"(d[17]), "+f"(d[18]), "+f"(d[19]), "+f"(d[20]), "+f"(d[21]), "+f"(d[22]), "+f"(d[23]), "+f"(d[24]), "+f"(d[25]), "+f"(d[26]), "+f"(d[27]), "+f"(d[28]), "+f"(d[29]), "+f"(d[30]), "+f"(d[31]), "+f"(d[32]), "+f"(d[33]), "+f"(d[34]), "+f"(d[35]), "+f"(d[36]), "+f"(d[37]), "+f"(d[38]), "+f"(d[39]), "+f"(d[40]), "+f"(d[41]), "+f"(d[42]), "+f"(d[43]), "+f"(d[44]), "+f"(d[45]), "+f"(d[46]), "+f"(d[47]), "+f"(d[48]), "+f"(d[49]), "+f"(d[50]), "+f"(d[51]), "+f"(d[52]), "+f"(d[53]), "+f"(d[54]), "+f"(d[55]), "+f"(d[56]), "+f"(d[57]), "+f"(d[58]), "+f"(d[59]), "+f"(d[60]), "+f"(d[61]), "+f"(d[62]), "+f"(d[63]), "+f"(d[64]), "+f"(d[65]), "+f"(d[66]), "+f"(d[67]), "+f"(d[68]), "+f"(d[69]), "+f"(d[70]), "+f"(d[71])
    : "l"(da), "l"(db), "r"(sc));
}
__device__ __forceinline__ void wgmma_ss_n24_t11(float (&d)[12], uint64_t da, uint64_t db, int sc) {
  asm volatile("{\n.reg .pred p;\nsetp.ne.b32 p, %14, 0;\n"
    "wgmma.mma_async.sync.aligned.m64n24k16.f32.bf16.bf16 {%0, %1, %2, %3, %4, %5, %6, %7, %8, %9, %10, %11}, %12, %13, p, 1, 1, 1, 1;\n}\n"
    : "+f"(d[0]), "+f"(d[1]), "+f"(d[2]), "+f"(d[3]), "+f"(d[4]), "+f"(d[5]), "+f"(d[6]), "+f"(d[7]), "+f"(d[8]), "+f"(d[9]), "+f"(d[10]), "+f"(d[11])
    : "l"(da), "l"(db), "r"(sc));
}
__device__ __forceinline__ void wgmma_rs_n80_t0(float (&d)[40], uint32_t a0, uint32_t a1, uint32_t a2, uint32_t a3, uint64_t db, int sc) {
  asm volatile("{\n.reg .pred p;\nsetp.ne.b32 p, %45, 0;\n"
    "wgmma.mma_async.sync.aligned.m64n80k16.f32.bf16.bf16 {%0, %1, %2, %3, %4, %5, %6, %7, %8, %9, %10, %11, %12, %13, %14, %15, %16, %17, %18, %19, %20, %21, %22, %23, %24, %25, %26, %27, %28, %29, %30, %31, %32, %33, %34, %35, %36, %37, %38, %39}, {%40, %41, %42, %43}, %44, p, 1, 1, 0;\n}\n"
    : "+f"(d[0]), "+f"(d[1]), "+f"(d[2]), "+f"(d[3]), "+f"(d[4]), "+f"(d[5]), "+f"(d[6]), "+f"(d[7]), "+f"(d[8]), "+f"(d[9]), "+f"(d[10]), "+f"(d[11]), "+f"(d[12]), "+f"(d[13]), "+f"(d[14]), "+f"(d[15]), "+f"(d[16]), "+f"(d[17]), "+f"(d[18]), "+f"(d[19]), "+f"(d[20]), "+f"(d[21]), "+f"(d[22]), "+f"(d[23]), "+f"(d[24]), "+f"(d[25]), "+f"(d[26]), "+f"(d[27]), "+f"(d[28]), "+f"(d[29]), "+f"(d[30]), "+f"(d[31]), "+f"(d[32]), "+f"(d[33]), "+f"(d[34]), "+f"(d[35]), "+f"(d[36]), "+f"(d[37]), "+f"(d[38]), "+f"(d[39])
    : "r"(a0), "r"(a1), "r"(a2), "r"(a3), "l"(db), "r"(sc));
}

__device__ __forceinline__ float warp_sum(float v) {
#pragma unroll
  for (int o = 16; o > 0; o >>= 1) v += __shfl_xor_sync(0xffffffffu, v, o);
  return v;
}
__device__ __forceinline__ void ln_rows(uint32_t (&v)[2][9]) {
  float sum[2], var[2], mean[2];
#pragma unroll
  for (int r = 0; r < 2; r++) { float s = 0.f;
#pragma unroll
    for (int i = 0; i < 9; i++) s += bf_lo(v[r][i]) + bf_hi(v[r][i]);
    sum[r] = s; }
#pragma unroll
  for (int o = 16; o > 0; o >>= 1) { sum[0] += __shfl_xor_sync(0xffffffffu, sum[0], o); sum[1] += __shfl_xor_sync(0xffffffffu, sum[1], o); }
#pragma unroll
  for (int r = 0; r < 2; r++) { mean[r] = sum[r] * (1.f / 576.f); float s = 0.f;
#pragma unroll
    for (int i = 0; i < 9; i++) { float a = bf_lo(v[r][i]) - mean[r], b = bf_hi(v[r][i]) - mean[r]; s = fmaf(a, a, s); s = fmaf(b, b, s); }
    var[r] = s; }
#pragma unroll
  for (int o = 16; o > 0; o >>= 1) { var[0] += __shfl_xor_sync(0xffffffffu, var[0], o); var[1] += __shfl_xor_sync(0xffffffffu, var[1], o); }
#pragma unroll
  for (int r = 0; r < 2; r++) {
    float m = rbf(mean[r]);
    float vv = rbf(var[r] * (1.f / 576.f));
    float den = rbf(sqrtf(rbf(vv + 1e-5f)));
    float inv = 1.f / den;
#pragma unroll
    for (int i = 0; i < 9; i++) {
      uint32_t d = pack2(bf_lo(v[r][i]) - m, bf_hi(v[r][i]) - m);
      v[r][i] = pack2(bf_lo(d) * inv, bf_hi(d) * inv);
    }
  }
}

__device__ __forceinline__ void phase0(const Params& p, int cta, int warp, int lane) {
  const int g = lane >> 2, j = lane & 3;
  const bool do_ln = cta < 128;
  const int row0 = cta * 16 + warp * 2;
  uint32_t xr[2][9];
  if (do_ln) {
#pragma unroll
    for (int r = 0; r < 2; r++)
#pragma unroll
      for (int i = 0; i < 9; i++) xr[r][i] = ldg32(p.xp + (row0 + r) * D_ + i * 64 + lane * 2);
  }
  const int gw = cta * 8 + warp;
  const bool do_fold = gw < 864;
  const int hm = gw / 9, cb = (gw % 9) * 64, mat = hm >> 5, hh = hm & 31;
  uint32_t bw[8][3];
  uint32_t a00[4], a01[2], a10[2], a11;
  if (do_fold) {
#pragma unroll
    for (int nb = 0; nb < 8; nb++) {
      const bf16* src = p.wqkv + (size_t)(cb + nb * 8 + g) * (3 * D_) + mat * D_ + hh * 18;
      bw[nb][0] = ldg32(src + 2 * j);
      bw[nb][1] = ldg32(src + 8 + 2 * j);
      bw[nb][2] = (j == 0) ? ldg32(src + 16) : 0u;
    }
    if (mat < 2) {
      const bf16* W = p.wphi + hh * 324;
      auto pr = [&](int d, int f) { return ldg16(W + d * 18 + f) | (ldg16(W + (d + 1) * 18 + f) << 16); };
      a00[0] = pr(2 * j, g); a00[1] = pr(2 * j, g + 8); a00[2] = pr(2 * j + 8, g); a00[3] = pr(2 * j + 8, g + 8);
      a01[0] = (j == 0) ? pr(16, g) : 0u; a01[1] = (j == 0) ? pr(16, g + 8) : 0u;
      a10[0] = (g < 2) ? pr(2 * j, 16 + g) : 0u; a10[1] = (g < 2) ? pr(2 * j + 8, 16 + g) : 0u;
      a11 = (g < 2 && j == 0) ? pr(16, 16 + g) : 0u;
    } else {
      auto pr = [&](int d, int f) { return (d == f ? 0x3F80u : 0u) | (d + 1 == f ? 0x3F800000u : 0u); };
      a00[0] = pr(2 * j, g); a00[1] = pr(2 * j, g + 8); a00[2] = pr(2 * j + 8, g); a00[3] = pr(2 * j + 8, g + 8);
      a01[0] = 0u; a01[1] = 0u;
      a10[0] = 0u; a10[1] = 0u;
      a11 = (g < 2 && j == 0) ? pr(16, 16 + g) : 0u;
    }
  }
  if (do_ln) {
    ln_rows(xr);
#pragma unroll
    for (int r = 0; r < 2; r++)
#pragma unroll
      for (int i = 0; i < 9; i++) *reinterpret_cast<uint32_t*>(g_xn + (row0 + r) * D_ + i * 64 + lane * 2) = xr[r][i];
    ln_rows(xr);
#pragma unroll
    for (int r = 0; r < 2; r++)
#pragma unroll
      for (int i = 0; i < 9; i++) *reinterpret_cast<uint32_t*>(g_h + (row0 + r) * D_ + i * 64 + lane * 2) = xr[r][i];
    bar_sync(1, 256);
    if (warp == 0 && lane == 0) signal(C_LN);
  } else {
    for (int i = (cta - 128) * 256 + warp * 32 + lane; i < 32 * 36 * 5; i += 1024) reinterpret_cast<float4*>(g_kv)[i] = make_float4(0.f, 0.f, 0.f, 0.f);
  }
  PROF(2);
  if (do_fold) {
    const int gi = hh >> 2, jj = hh & 3;
    bf16* dst = (mat == 0) ? (g_wtq + gi * 72 * D_) : (g_wtkv + (gi * 144 + (mat == 2 ? 72 : 0)) * D_);
    bf16* d0 = dst + (8 * (g >> 1) + 2 * jj + (g & 1)) * D_ + cb + 2 * j;
    bf16* d1 = d0 + 32 * D_;
    bf16* d2 = d0 + 64 * D_;
#pragma unroll
    for (int nb = 0; nb < 8; nb++) {
      float c0[4] = {0.f, 0.f, 0.f, 0.f}, c1[4] = {0.f, 0.f, 0.f, 0.f};
      mma16816(c0, a00[0], a00[1], a00[2], a00[3], bw[nb][0], bw[nb][1]);
      mma16816(c0, a01[0], a01[1], 0u, 0u, bw[nb][2], 0u);
      mma16816(c1, a10[0], 0u, a10[1], 0u, bw[nb][0], bw[nb][1]);
      mma16816(c1, a11, 0u, 0u, 0u, bw[nb][2], 0u);
      *reinterpret_cast<uint32_t*>(d0 + nb * 8) = pack2(c0[0], c0[1]);
      *reinterpret_cast<uint32_t*>(d1 + nb * 8) = pack2(c0[2], c0[3]);
      if (g < 2) *reinterpret_cast<uint32_t*>(d2 + nb * 8) = pack2(c1[0], c1[1]);
    }
  }
  bar_sync(1, 256);
  if (warp == 0 && lane == 0) signal(C_PREP);
}

__device__ __forceinline__ void mlp_mainloop(float (&acc)[96], int nkb, int& it, uint32_t sbase, int wg, int t) {
  const uint32_t bars = sbase + OFF_BAR;
  for (int kb = 0; kb < nkb; kb++, it++) {
    const int s = it & 3;
    mbar_wait(bars + B_FULL + 8 * s, (it >> 2) & 1);
    const uint32_t sa = sbase + s * MLP_STAGE + wg * 8192, sb = sbase + s * MLP_STAGE + 16384;
    const uint64_t da = make_desc(sa, 8192, 1024, 1), db = make_desc(sb, 8192, 1024, 1);
    wgmma_fence();
#pragma unroll
    for (int kk = 0; kk < 4; kk++) wgmma_ss_n192_t11(acc, da + kk * 128, db + kk * 128, (kb | kk) != 0);
    wgmma_commit();
    if (kb > 0) { wgmma_wait<1>(); if (t == 0) mbar_arrive(bars + B_EMPTY + 8 * ((it - 1) & 3)); }
  }
  wgmma_wait<0>();
  if (t == 0) mbar_arrive(bars + B_EMPTY + 8 * ((it - 1) & 3));
}

__device__ __forceinline__ void g1_epilogue(const Params& p, float (&acc)[96], float hb0, float hb1, uint32_t sbase, int wg, int t, int f, int j, int rank) {
  const int lane = t & 31, w4 = t >> 5;
  const uint32_t stg = sbase + OFF_USTG + wg * 24576;
  const int m = lane >> 3, row = w4 * 16 + (m & 1) * 8 + (lane & 7);
  const uint32_t rowaddr = stg + row * 128;
  constexpr float GA = 0.28541926f, GB = 1.5957691216f;
#pragma unroll
  for (int i = 0; i < 24; i += 2) {
    uint32_t r[4];
#pragma unroll
    for (int q = 0; q < 4; q++) {
      const float hb = (q & 1) ? hb1 : hb0;
      const float h0 = fmaf(acc[4 * i + 2 * q], 0.5f, hb), h1 = fmaf(acc[4 * i + 2 * q + 1], 0.5f, hb);
      const float t0 = tanh_fast(h0 * fmaf(h0 * h0, GA, GB)), t1 = tanh_fast(h1 * fmaf(h1 * h1, GA, GB));
      r[q] = pack2(fmaf(h0, t0, h0), fmaf(h1, t1, h1));
    }
    const int blk = i + (m >> 1);
    stsm4(rowaddr + (blk >> 3) * 8192 + (((blk & 7) ^ (row & 7)) << 4), r[0], r[1], r[2], r[3]);
  }
  fence_async_smem();
  bar_sync(4 + wg, 128);
  if (t == 0) {
    tma_st_3d(&p.u, stg, 0, f * 128 + wg * 64, j * 3);
    bulk_commit();
    bulk_wait0();
    signal(C_U + j * 2 + rank);
  }
}

template <int P>
__device__ __forceinline__ void g2_tail(const Params& p, float (&acc)[96], int& it, uint32_t sbase, int wg, int t, int i_s, int j) {
  const uint32_t bars = sbase + OFF_BAR;
  const int lane = t & 31, w4 = t >> 5, tid = wg * 128 + t;
  const uint32_t xbuf = sbase + OFF_USTG + tid * 16;
  const uint32_t rbuf = mapa(xbuf, P ^ 1), rbar = mapa(bars + B_XCH, P ^ 1);
  const int grow = i_s * 128 + wg * 64 + w4 * 16 + (lane >> 2);
  const float b2a = __bfloat162float(p.b2[grow]), b2b = __bfloat162float(p.b2[grow + 8]);
  mbar_wait_cluster(bars + B_XRDY, 0);
  float sacc[48];
#pragma unroll
  for (int kb = 0; kb < 9; kb++, it++) {
    const int s = it & 3;
    mbar_wait(bars + B_FULL + 8 * s, (it >> 2) & 1);
    const uint32_t sa = sbase + s * MLP_STAGE + wg * 8192, sb = sbase + s * MLP_STAGE + 16384;
    const uint64_t da = make_desc(sa, 16, 1024, 1), db = make_desc(sb, 8192, 1024, 1);
    wgmma_fence();
#pragma unroll
    for (int kk = 0; kk < 4; kk++) wgmma_ss_n96_t01(sacc, da + kk * 2, db + kk * 128, (kb | kk) != 0);
    wgmma_commit();
    if (kb < 6) {
#pragma unroll
      for (int q = 2 * kb; q < 2 * kb + 2; q++) {
        const int a = (P ^ 1) * 48 + 4 * q;
        asm volatile("st.async.weak.shared::cluster.mbarrier::complete_tx::bytes.v4.f32 [%0], {%1, %2, %3, %4}, [%5];"
          :: "r"(rbuf + q * 4096), "f"(acc[a]), "f"(acc[a + 1]), "f"(acc[a + 2]), "f"(acc[a + 3]), "r"(rbar + (q / 3) * 8) : "memory");
      }
    }
    if (kb > 0) { wgmma_wait<1>(); if (t == 0) mbar_arrive(bars + B_EMPTY + 8 * ((it - 1) & 3)); }
  }
  PROF(20 + wg);
#pragma unroll
  for (int c = 0; c < 4; c++) {
    mbar_wait_cluster(bars + B_XCH + 8 * c, 0);
#pragma unroll
    for (int q = 3 * c; q < 3 * c + 3; q++) {
      float4 v;
      asm volatile("ld.shared.v4.f32 {%0, %1, %2, %3}, [%4];" : "=f"(v.x), "=f"(v.y), "=f"(v.z), "=f"(v.w) : "r"(xbuf + q * 4096) : "memory");
      const int a = P * 48 + 4 * q;
      const float y0 = 0.5f * (acc[a] + v.x + b2a), y1 = 0.5f * (acc[a + 1] + v.y + b2a), y2 = 0.5f * (acc[a + 2] + v.z + b2b), y3 = 0.5f * (acc[a + 3] + v.w + b2b);
      acc[a] = fmaf(y0, tanh_fast(y0), y0); acc[a + 1] = fmaf(y1, tanh_fast(y1), y1);
      acc[a + 2] = fmaf(y2, tanh_fast(y2), y2); acc[a + 3] = fmaf(y3, tanh_fast(y3), y3);
    }
  }
  wgmma_wait<0>();
  if (t == 0) mbar_arrive(bars + B_EMPTY + 8 * ((it - 1) & 3));
  PROF(22 + wg);
  {
    const int s = it & 3;
    mbar_wait(bars + B_FULL + 8 * s, (it >> 2) & 1);
    const uint32_t xs = sbase + s * MLP_STAGE + wg * 12288;
    const int m = lane >> 3, row = w4 * 16 + (m & 1) * 8 + (lane & 7);
#pragma unroll
    for (int i = 0; i < 12; i += 2) {
      const int blk = i + (m >> 1);
      const uint32_t addr = xs + (blk >> 2) * 4096 + row * 64 + (((blk & 3) ^ ((row >> 1) & 3)) << 4);
      uint32_t r[4];
      ldsm4(addr, r[0], r[1], r[2], r[3]);
#pragma unroll
      for (int q = 0; q < 4; q++) {
        const int a = 4 * i + 2 * q;
        r[q] = pack2(fmaf(sacc[a], acc[P * 48 + a], bf_lo(r[q])), fmaf(sacc[a + 1], acc[P * 48 + a + 1], bf_hi(r[q])));
      }
      stsm4(addr, r[0], r[1], r[2], r[3]);
    }
    fence_async_smem();
    bar_sync(4 + wg, 128);
    if (t == 0) {
      tma_st_3d(&p.out, xs, 0, i_s * 128 + wg * 64, j * 6 + P * 3);
      bulk_commit();
      bulk_wait0();
    }
    it++;
  }
}

__device__ __forceinline__ void att_mainloop(float (&a0)[72], float (&a1)[72], int it0, uint32_t sbase, int t) {
  const uint32_t bars = sbase + OFF_BAR;
  for (int kb = 0; kb < 9; kb++) {
    const int it = it0 + kb, s = it & 3;
    mbar_wait(bars + B_FULL + 8 * s, (it >> 2) & 1);
    const uint32_t sa = sbase + s * ATT_STAGE, sb = sa + 16384;
    const uint64_t da = make_desc(sa, 16, 1024, 1), db = make_desc(sb, 16, 1024, 1);
    wgmma_fence();
#pragma unroll
    for (int kk = 0; kk < 4; kk++) {
      wgmma_ss_n144_t00(a0, da + kk * 2, db + kk * 2, (kb | kk) != 0);
      wgmma_ss_n144_t00(a1, da + 512 + kk * 2, db + kk * 2, (kb | kk) != 0);
    }
    wgmma_commit();
    if (kb > 0) { wgmma_wait<1>(); if (t < 2) mbar_arrive(bars + B_EMPTY + 8 * ((it - 1) & 3)); }
  }
}

template <int OFF>
__device__ __forceinline__ void dual_softmax(const float (&a)[72], uint32_t (&P)[18]) {
  constexpr float L2E = 1.4426950408889634f;
  float mx = a[OFF], mn = a[OFF];
#pragma unroll
  for (int i = 1; i < 18; i++) { const float v = a[OFF + 4 * (i >> 1) + (i & 1)]; mx = fmaxf(mx, v); mn = fminf(mn, v); }
  const float cp = -mx * L2E, cn = mn * L2E;
  float e[18], sum = 0.f;
#pragma unroll
  for (int i = 0; i < 18; i++) { e[i] = ex2(fmaf(a[OFF + 4 * (i >> 1) + (i & 1)], L2E, cp)); sum += e[i]; }
  float inv = rcp_fast(sum);
#pragma unroll
  for (int i = 0; i < 9; i++) P[i] = pack2(e[2 * i] * inv, e[2 * i + 1] * inv);
  sum = 0.f;
#pragma unroll
  for (int i = 0; i < 18; i++) { e[i] = ex2(fmaf(a[OFF + 4 * (i >> 1) + (i & 1)], -L2E, cn)); sum += e[i]; }
  inv = rcp_fast(sum);
#pragma unroll
  for (int i = 0; i < 9; i++) P[9 + i] = pack2(e[2 * i] * inv, e[2 * i + 1] * inv);
}

__device__ __forceinline__ void a1_block(const float (&a)[72], float (&kv0)[12], float (&kv1)[12], float (&kv2)[12], float (&kv3)[12],
                                         uint32_t stg, int wg, int t) {
  const int lane = t & 31, w4 = t >> 5, g = lane >> 2, j = lane & 3;
  const uint32_t ph = opaque(stg) + j * PH_HS + (w4 * 2) * 640 + g * 16, vv = opaque(stg) + 4 * PH_HS + j * V_HS + (w4 * 2) * 384 + g * 16;
  {
    uint32_t P[18];
    dual_softmax<0>(a, P);
#pragma unroll
    for (int c = 0; c < 4; c++) sts128(ph + c * 128, P[4 * c], P[4 * c + 1], P[4 * c + 2], P[4 * c + 3]);
    sts64(ph + 512, P[16], P[17]);
    dual_softmax<2>(a, P);
#pragma unroll
    for (int c = 0; c < 4; c++) sts128(ph + 640 + c * 128, P[4 * c], P[4 * c + 1], P[4 * c + 2], P[4 * c + 3]);
    sts64(ph + 640 + 512, P[16], P[17]);
  }
#pragma unroll
  for (int r = 0; r < 2; r++) {
    uint32_t q[9];
#pragma unroll
    for (int i = 0; i < 9; i++) q[i] = pack2(a[36 + 4 * i + 2 * r], a[36 + 4 * i + 2 * r + 1]);
    sts128(vv + r * 384, q[0], q[1], q[2], q[3]);
    sts128(vv + r * 384 + 128, q[4], q[5], q[6], q[7]);
    sts64(vv + r * 384 + 256, q[8], 0x00003F80u);
  }
  fence_async_smem();
  bar_sync(4 + wg, 128);
  const uint32_t so = opaque(stg);
  const uint64_t da = make_desc(so, 640, 128, 0), db = make_desc(so + 4 * PH_HS, 384, 128, 0);
  wgmma_fence();
#pragma unroll
  for (int ks = 0; ks < 4; ks++) {
    const int sc = ks > 0;
    wgmma_ss_n24_t11(kv0, da + (0 * PH_HS + ks * 1280) / 16, db + (0 * V_HS + ks * 768) / 16, sc);
    wgmma_ss_n24_t11(kv1, da + (1 * PH_HS + ks * 1280) / 16, db + (1 * V_HS + ks * 768) / 16, sc);
    wgmma_ss_n24_t11(kv2, da + (2 * PH_HS + ks * 1280) / 16, db + (2 * V_HS + ks * 768) / 16, sc);
    wgmma_ss_n24_t11(kv3, da + (3 * PH_HS + ks * 1280) / 16, db + (3 * V_HS + ks * 768) / 16, sc);
  }
  wgmma_commit();
  wgmma_wait<0>();
  bar_sync(4 + wg, 128);
}
__device__ __forceinline__ void kv_flush(const float (&kv)[12], int head, int t) {
  const int lane = t & 31, w4 = t >> 5, g = lane >> 2, j = lane & 3;
  float* base = g_kv + head * 720 + 2 * j;
#pragma unroll
  for (int r = 0; r < 2; r++) {
    const int f = w4 * 16 + g + 8 * r;
    if (f < 36) {
#pragma unroll
      for (int i = 0; i < 2; i++)
        asm volatile("red.global.add.v2.f32 [%0], {%1, %2};" :: "l"(base + f * 20 + 8 * i), "f"(kv[4 * i + 2 * r]), "f"(kv[4 * i + 2 * r + 1]) : "memory");
      if (j < 2) asm volatile("red.global.add.v2.f32 [%0], {%1, %2};" :: "l"(base + f * 20 + 16), "f"(kv[8 + 2 * r]), "f"(j == 0 ? kv[8 + 2 * r + 1] : 0.f) : "memory");
    }
  }
}

__device__ __forceinline__ void a2_group(const float (&a)[72], uint32_t kvb, uint32_t ostg, int t) {
  const int lane = t & 31, w4 = t >> 5, g = lane >> 2, j = lane & 3;
  uint32_t P0[18], P1[18];
  dual_softmax<0>(a, P0);
  dual_softmax<2>(a, P1);
  float o[40];
  const uint64_t db = make_desc(opaque(kvb), 1280, 128, 0);
  wgmma_fence();
#pragma unroll
  for (int ks = 0; ks < 9; ks++) wgmma_rs_n80_t0(o, P0[2 * ks], P1[2 * ks], P0[2 * ks + 1], P1[2 * ks + 1], db + ks * 160, ks != 0);
  wgmma_commit();
  wgmma_wait<0>();
  const float i0 = 1.f / (o[36] + 1e-6f), i1 = 1.f / (o[38] + 1e-6f);
  const uint32_t dst = ostg + (w4 * 16 + g) * 288 + j * 36;
#pragma unroll
  for (int i = 0; i < 9; i++) {
    sts32(dst + 4 * i, pack2(o[4 * i] * i0, o[4 * i + 1] * i0));
    sts32(dst + 8 * 288 + 4 * i, pack2(o[4 * i + 2] * i1, o[4 * i + 3] * i1));
  }
}
__device__ __forceinline__ void build_kvb(uint32_t kvb, int oct, int t) {
  for (int c = t; c < 2880; c += 128) {
    const int grp = c / 1440, r = c % 1440, ks = r / 160, kc = (r / 80) & 1, n = r % 80;
    const int i = n >> 3, jn = (n >> 1) & 3, e = n & 1;
    const int f = 4 * ks + 2 * kc, col = (i < 9) ? 2 * i + e : 18;
    const float* src = g_kv + (oct * 8 + grp * 4 + jn) * 720 + f * 20 + col;
    uint32_t w = 0;
    if (i < 9 || e == 0) w = pack2(__ldcg(src), __ldcg(src + 20));
    sts128(kvb + grp * KVB_BYTES + ks * 2560 + kc * 1280 + (n >> 3) * 128 + (n & 7) * 16, jn == 0 ? w : 0u, jn == 1 ? w : 0u, jn == 2 ? w : 0u, jn == 3 ? w : 0u);
  }
}

__device__ __forceinline__ void att_consumer(const Params& p, int slot, int it_base, uint32_t sbase, int wg, int t) {
  const int n = p.nitems[slot];
  const uint32_t bars = sbase + OFF_BAR;
  bool kvb_seen = false;
  int first_a2 = n;
  for (int k = 0; k < n; k++) if (p.items[slot][k] >> 7) { first_a2 = k; break; }
  for (int k = wg; k < n; k += 2) {
    const int item = p.items[slot][k], type = item >> 7, rb = (item >> 3) & 15, g = item & 7;
    float a0[72], a1[72];
    if (k > 0) bar_sync(2 + wg, 256);
    att_mainloop(a0, a1, it_base + k * 9, sbase, t);
    if (k + 1 < n) bar_arrive(2 + (wg ^ 1), 256);
    wgmma_wait<0>();
    if (t < 2) mbar_arrive(bars + B_EMPTY + 8 * ((it_base + k * 9 + 8) & 3));
    PROF(24 + 2 * k);
    if (type == 0) {
      const uint32_t stg = sbase + OFF_ATT + wg * A1_STG;
#pragma unroll 1
      for (int mb = 0; mb < 2; mb++) {
        float kv0[12], kv1[12], kv2[12], kv3[12];
        a1_block(a0, kv0, kv1, kv2, kv3, stg, wg, t);
        kv_flush(kv0, g * 4 + 0, t); kv_flush(kv1, g * 4 + 1, t); kv_flush(kv2, g * 4 + 2, t); kv_flush(kv3, g * 4 + 3, t);
#pragma unroll
        for (int i = 0; i < 72; i++) a0[i] = a1[i];
      }
      bar_sync(4 + wg, 128);
      if (t == 0) { __threadfence(); signal(C_KV); }
    } else {
      const uint32_t kvb = sbase + OFF_ATT, ostg = sbase + OFF_OSTG + wg * 18432;
      if (!kvb_seen) {
        if (k == first_a2) {
          if (t == 0) wait_cnt(C_KV, 128);
          bar_sync(4 + wg, 128);
          build_kvb(kvb, g, t);
          fence_async_smem();
          mbar_arrive(bars + B_KVB);
        }
        mbar_wait(bars + B_KVB, 0);
        kvb_seen = true;
      }
#pragma unroll 1
      for (int q = 0; q < 4; q++) {
        a2_group(a0, kvb + (q & 1) * KVB_BYTES, ostg + (q & 1) * 144, t);
        if (q & 1) {
          fence_async_smem();
          bar_sync(4 + wg, 128);
          if (t == 0) {
            tma_st_2d(&p.o_st, ostg, g * 144, rb * 128 + (q >> 1) * 64);
            bulk_commit();
            if (q == 1) bulk_wait0_read(); else { bulk_wait0(); signal(C_O + rb); }
          }
          bar_sync(4 + wg, 128);
        }
#pragma unroll
        for (int i = 0; i < 36; i++) { a0[i] = a0[36 + i]; a0[36 + i] = a1[i]; a1[i] = a1[36 + i]; }
      }
    }
    PROF(25 + 2 * k);
  }
}

__device__ __forceinline__ void att_producer(const Params& p, int slot, int it, uint32_t sbase) {
  const uint32_t bars = sbase + OFF_BAR;
  const int n = p.nitems[slot];
  for (int k = 0; k < n; k++) {
    const int item = p.items[slot][k], type = item >> 7, rb = (item >> 3) & 15, g = item & 7;
    const CUtensorMap* mb = type ? &p.wq : &p.wkv;
    for (int kb = 0; kb < 9; kb++, it++) {
      const int s = it & 3;
      const uint32_t full = bars + B_FULL + 8 * s, sa = sbase + s * ATT_STAGE;
      mbar_wait(bars + B_EMPTY + 8 * s, ((it >> 2) & 1) ^ 1);
      mbar_expect_tx(full, 16384 + 18432);
      tma_2d(sa, &p.xn, full, kb * 64, rb * 128);
      tma_2d(sa + 16384, mb, full, kb * 64, g * 144);
    }
  }
}

__global__ void __cluster_dims__(2, 1, 1) __launch_bounds__(384, 1) fused_kernel(const __grid_constant__ Params p) {
  extern __shared__ uint8_t smem_raw[];
  const uint32_t sbase = (smem_u32(smem_raw) + 1023) & ~1023u;
  const uint32_t bars = sbase + OFF_BAR;
  const int wg = threadIdx.x >> 7, t = threadIdx.x & 127;
  const int cta = blockIdx.x, rank = cta & 1;
  const int role = p.role[cta >> 1];
  const bool is_mlp = role < 54;
  const int fi = role / 3, j = role % 3;
  const bool owner = is_mlp && fi < 16;
  const int slot = is_mlp ? (24 + (fi - 16) * 6 + j * 2 + rank) : ((role - 54) * 2 + rank);
  PROF(0);
  if (threadIdx.x == 0) {
    for (int s = 0; s < 4; s++) { mbar_init(bars + B_FULL + 8 * s, 1); mbar_init(bars + B_EMPTY + 8 * s, 2); mbar_init(bars + B_XCH + 8 * s, 1); }
    mbar_init(bars + B_XRDY, 2);
    mbar_init(bars + B_KVB, 128);
    asm volatile("fence.mbarrier_init.release.cluster;" ::: "memory");
    for (int c = 0; c < 4; c++) mbar_expect_tx(bars + B_XCH + 8 * c, 12288);
  }
  __syncthreads();
  asm volatile("barrier.cluster.arrive.release.aligned;\nbarrier.cluster.wait.acquire.aligned;" ::: "memory");

  if (wg == 2) {
    asm volatile("setmaxnreg.dec.sync.aligned.u32 40;");
    if (t == 0) {
      int it = 0;
      if (is_mlp) {
        prefetch_map(&p.w1); prefetch_map(&p.h); prefetch_map(&p.w2); prefetch_map(&p.u);
        const int f = fi + 18 * rank;
        for (int s = 0; s < 4; s++) { mbar_expect_tx(bars + B_FULL + 8 * s, MLP_STAGE); tma_3d(sbase + s * MLP_STAGE, &p.w1, bars + B_FULL + 8 * s, 0, s * 64, f * 2); }
        wait_cnt(C_LN, 128);
        fence_async_all();
        PROF1(3);
        for (int s = 0; s < 4; s++) tma_3d(sbase + s * MLP_STAGE + 16384, &p.h, bars + B_FULL + 8 * s, 0, s * 64, j * 3);
        for (it = 4; it < 32; it++) {
          const int s = it & 3;
          const uint32_t full = bars + B_FULL + 8 * s, sa = sbase + s * MLP_STAGE;
          mbar_wait(bars + B_EMPTY + 8 * s, ((it >> 2) & 1) ^ 1);
          mbar_expect_tx(full, MLP_STAGE);
          tma_3d(sa, &p.w1, full, 0, it * 64, f * 2);
          tma_3d(sa + 16384, &p.h, full, 0, it * 64, j * 3);
        }
        if (owner) {
          const int k0 = rank * 2304;
          for (int kb = 0; kb < 4; kb++) {
            const int s = (it + kb) & 3;
            mbar_wait(bars + B_EMPTY + 8 * s, (((it + kb) >> 2) & 1) ^ 1);
            mbar_expect_tx(bars + B_FULL + 8 * s, MLP_STAGE);
            tma_3d(sbase + s * MLP_STAGE, &p.w2, bars + B_FULL + 8 * s, 0, k0 + kb * 64, fi * 2);
          }
          wait_cnt(C_U + j * 2 + rank, 36);
          fence_async_all();
          PROF1(6);
          for (int kb = 0; kb < 4; kb++) { const int s = (it + kb) & 3; tma_3d(sbase + s * MLP_STAGE + 16384, &p.u, bars + B_FULL + 8 * s, 0, k0 + kb * 64, j * 3); }
          it += 4;
          for (int kb = 4; kb < 36; kb++, it++) {
            const int s = it & 3;
            const uint32_t full = bars + B_FULL + 8 * s, sa = sbase + s * MLP_STAGE;
            mbar_wait(bars + B_EMPTY + 8 * s, ((it >> 2) & 1) ^ 1);
            mbar_expect_tx(full, MLP_STAGE);
            tma_3d(sa, &p.w2, full, 0, k0 + kb * 64, fi * 2);
            tma_3d(sa + 16384, &p.u, full, 0, k0 + kb * 64, j * 3);
          }
          wait_cnt(C_O + fi, 4);
          fence_async_all();
          const int c0 = j * 192 + rank * 96;
          for (int kb = 0; kb < 9; kb++, it++) {
            const int s = it & 3;
            const uint32_t full = bars + B_FULL + 8 * s, sa = sbase + s * MLP_STAGE;
            mbar_wait(bars + B_EMPTY + 8 * s, ((it >> 2) & 1) ^ 1);
            mbar_expect_tx(full, 32768);
            tma_2d(sa, &p.o_ld, full, kb * 64, fi * 128);
            tma_2d(sa + 16384, &p.wo, full, c0, kb * 64);
            tma_2d(sa + 16384 + 8192, &p.wo, full, c0 + 64, kb * 64);
          }
          {
            const int s = it & 3;
            const uint32_t full = bars + B_FULL + 8 * s, sa = sbase + s * MLP_STAGE;
            mbar_wait(bars + B_EMPTY + 8 * s, ((it >> 2) & 1) ^ 1);
            mbar_expect_tx(full, 24576);
            tma_3d(sa, &p.x, full, 0, fi * 128, j * 6 + rank * 3);
            tma_3d(sa + 12288, &p.x, full, 0, fi * 128 + 64, j * 6 + rank * 3);
          }
        }
      }
      if (!owner) {
        prefetch_map(&p.xn); prefetch_map(&p.wkv); prefetch_map(&p.wq);
        wait_cnt(C_PREP, NCTA);
        fence_async_all();
        PROF1(7);
        att_producer(p, slot, it, sbase);
      }
    }
  } else {
    asm volatile("setmaxnreg.inc.sync.aligned.u32 232;");
    phase0(p, cta, threadIdx.x >> 5, threadIdx.x & 31);
    PROF(4);
    int it = 0;
    if (is_mlp) {
      const int f = fi + 18 * rank;
      const int brow = f * 128 + wg * 64 + (t >> 5) * 16 + ((t & 31) >> 2);
      const float hb0 = 0.5f * __bfloat162float(p.b1[brow]), hb1 = 0.5f * __bfloat162float(p.b1[brow + 8]);
      float acc[96];
      mlp_mainloop(acc, 32, it, sbase, wg, t);
      PROF(8 + wg);
      g1_epilogue(p, acc, hb0, hb1, sbase, wg, t, f, j, rank);
      if (t == 0) mbar_arrive_remote(mapa(bars + B_XRDY, rank ^ 1));
      PROF(10 + wg);
      if (owner) {
        mlp_mainloop(acc, 36, it, sbase, wg, t);
        PROF(12 + wg);
        if (rank == 0) g2_tail<0>(p, acc, it, sbase, wg, t, fi, j);
        else g2_tail<1>(p, acc, it, sbase, wg, t, fi, j);
      } else {
        bar_sync(1, 256);
      }
    }
    if (!owner) att_consumer(p, slot, it, sbase, wg, t);
    PROF(14 + wg);
    bar_sync(1, 256);
    if (threadIdx.x == 0) {
      __threadfence();
      if (atomicAdd(&g_cnt[C_DONE * 32], 1u) == NCTA - 1) {
        for (int c = 0; c < C_NUM; c++) g_cnt[c * 32] = 0u;
        __threadfence();
      }
    }
  }
}

typedef CUresult (*EncodeTiledFn)(CUtensorMap*, CUtensorMapDataType, cuuint32_t, void*, const cuuint64_t*, const cuuint64_t*, const cuuint32_t*,
                                  const cuuint32_t*, CUtensorMapInterleave, CUtensorMapSwizzle, CUtensorMapL2promotion, CUtensorMapFloatOOBfill);

void map2d(EncodeTiledFn enc, CUtensorMap* m, const void* ptr, uint64_t rows, uint64_t cols, uint32_t br, uint32_t bc, CUtensorMapSwizzle sw) {
  cuuint64_t dims[2] = {cols, rows}; cuuint64_t strides[1] = {cols * 2}; cuuint32_t box[2] = {bc, br}; cuuint32_t es[2] = {1, 1};
  enc(m, CU_TENSOR_MAP_DATA_TYPE_BFLOAT16, 2, (void*)ptr, dims, strides, box, es, CU_TENSOR_MAP_INTERLEAVE_NONE, sw,
      CU_TENSOR_MAP_L2_PROMOTION_L2_128B, CU_TENSOR_MAP_FLOAT_OOB_FILL_NONE);
}
void map3d(EncodeTiledFn enc, CUtensorMap* m, const void* ptr, uint64_t rows, uint64_t cols, uint32_t cw, uint32_t br, uint32_t nch, CUtensorMapSwizzle sw) {
  cuuint64_t dims[3] = {cw, rows, cols / cw}; cuuint64_t strides[2] = {cols * 2, (cuuint64_t)cw * 2}; cuuint32_t box[3] = {cw, br, nch}; cuuint32_t es[3] = {1, 1, 1};
  enc(m, CU_TENSOR_MAP_DATA_TYPE_BFLOAT16, 3, (void*)ptr, dims, strides, box, es, CU_TENSOR_MAP_INTERLEAVE_NONE, sw,
      CU_TENSOR_MAP_L2_PROMOTION_L2_128B, CU_TENSOR_MAP_FLOAT_OOB_FILL_NONE);
}

void build_schedule(Params& p) {
  int gpc_clusters[8][9], cnt[8] = {0};
  for (int c = 0; c < 66; c++) {
    int g;
    if (c < 4) g = 0; else if (c < 36) g = (c - 4) % 8; else if (c < 64) g = (c - 36) % 7 + 1; else g = 6 + (c - 64);
    gpc_clusters[g][cnt[g]++] = c;
  }
  int att = 0;
  for (int g = 0; g < 8; g++) {
    int k = 0;
    for (int q = 0; q < 2; q++) for (int j = 0; j < 3; j++) p.role[gpc_clusters[g][k++]] = (uint8_t)((2 * g + q) * 3 + j);
    if (g < 6) { p.role[gpc_clusters[g][k++]] = (uint8_t)(54 + att++); p.role[gpc_clusters[g][k++]] = (uint8_t)(54 + att++); }
    else for (int j = 0; j < 3; j++) p.role[gpc_clusters[g][k++]] = (uint8_t)((16 + (g - 6)) * 3 + j);
  }
  for (int s = 0; s < NATT; s++) p.nitems[s] = 0;
  auto add = [&](int slot, int type, int rb, int g) { p.items[slot][p.nitems[slot]++] = (uint8_t)((type << 7) | (rb << 3) | g); };
  int blk = 0;
  for (int step = 0; step < 5; step++)
    for (int quad = 0; quad < 6; quad++, blk++)
      for (int q = 0; q < 4; q++) add(quad * 4 + q, 0, (blk / 4) * 2 + (q & 1), (blk % 4) * 2 + (q >> 1));
  for (int b = 0; b < 2; b++, blk++)
    for (int q = 0; q < 4; q++) add(24 + 4 + b * 4 + q, 0, (blk / 4) * 2 + (q & 1), (blk % 4) * 2 + (q >> 1));
  int next_rb[4] = {0, 0, 0, 0};
  for (int s = 0; s < 24; s++) for (int r = 0; r < 2; r++) add(s, 1, next_rb[s % 4]++, s % 4);
  for (int s = 24; s < 36; s++) for (int r = 0; r < (s < 28 ? 2 : 1); r++) add(s, 1, next_rb[s % 4]++, s % 4);
}

}

extern "C" void kernel_launch(void* const* d_in, const int* in_sizes, int n_in, void* d_out, int out_size) {
  (void)in_sizes; (void)n_in; (void)out_size;
  static EncodeTiledFn enc = nullptr;
  static void *xn, *h, *u, *o, *wtkv, *wtq;
  if (!enc) {
    void* fn = nullptr; cudaDriverEntryPointQueryResult q;
    cudaGetDriverEntryPoint("cuTensorMapEncodeTiled", &fn, cudaEnableDefault, &q);
    enc = (EncodeTiledFn)fn;
    cudaGetSymbolAddress(&xn, g_xn); cudaGetSymbolAddress(&h, g_h); cudaGetSymbolAddress(&u, g_u); cudaGetSymbolAddress(&o, g_o);
    cudaGetSymbolAddress(&wtkv, g_wtkv); cudaGetSymbolAddress(&wtq, g_wtq);
    cudaFuncSetAttribute(fused_kernel, cudaFuncAttributeMaxDynamicSharedMemorySize, SMEM_BYTES);
  }
  const bf16* x = (const bf16*)d_in[0];
  const bf16* wqkv = (const bf16*)d_in[1];
  const bf16* wphi = (const bf16*)d_in[2];
  const bf16* wo = (const bf16*)d_in[3];
  const bf16* w1 = (const bf16*)d_in[5];
  const bf16* b1 = (const bf16*)d_in[6];
  const bf16* w2 = (const bf16*)d_in[7];
  const bf16* b2 = (const bf16*)d_in[8];
  Params p;
  const CUtensorMapSwizzle S128 = CU_TENSOR_MAP_SWIZZLE_128B, S64 = CU_TENSOR_MAP_SWIZZLE_64B, S0 = CU_TENSOR_MAP_SWIZZLE_NONE;
  map3d(enc, &p.w1, w1, S_, F_, 64, 64, 2, S128);
  map3d(enc, &p.h, h, S_, D_, 64, 64, 3, S128);
  map3d(enc, &p.w2, w2, F_, S_, 64, 64, 2, S128);
  map3d(enc, &p.u, u, F_, D_, 64, 64, 3, S128);
  map2d(enc, &p.xn, xn, S_, D_, 128, 64, S128);
  map2d(enc, &p.wkv, wtkv, 8 * 144, D_, 144, 64, S128);
  map2d(enc, &p.wq, wtq, 8 * 72, D_, 144, 64, S128);
  map2d(enc, &p.o_st, o, S_, D_, 64, 144, S0);
  map2d(enc, &p.o_ld, o, S_, D_, 128, 64, S128);
  map2d(enc, &p.wo, wo, D_, D_, 64, 64, S128);
  map3d(enc, &p.x, x, S_, D_, 32, 64, 3, S64);
  map3d(enc, &p.out, d_out, S_, D_, 32, 64, 3, S64);
  p.xp = x; p.wqkv = wqkv; p.wphi = wphi; p.b1 = b1; p.b2 = b2;
  build_schedule(p);
  fused_kernel<<<NCTA, 384, SMEM_BYTES>>>(p);
}
```

```cpp
#include <cuda_runtime.h>
#include <cuda_bf16.h>
#include <cuda.h>
#include <stdint.h>

namespace {

typedef __nv_bfloat16 bf16;
constexpr int S_ = 2048, D_ = 576, F_ = 4608;
constexpr int NCTA = 132;
constexpr int NATT = 36;
constexpr int MAXITEMS = 10;
constexpr int NKV = 56;

constexpr int MLP_STAGE = 40960;
constexpr int ATT_STAGE = 34816;
constexpr int OFF_USTG = 4 * MLP_STAGE;
constexpr int OFF_ATT = 4 * ATT_STAGE;
constexpr int PH_HS = 5152, V_HS = 3104;
constexpr int A1_STG = 4 * PH_HS + 4 * V_HS;
constexpr int KVB_BYTES = 23040;
constexpr int OFF_OSTG = OFF_ATT + 2 * KVB_BYTES;
constexpr int OFF_BAR = 222208;
constexpr int SMEM_BYTES = OFF_BAR + 256 + 1024;
constexpr int B_FULL = 0, B_EMPTY = 32, B_XCH = 64, B_XRDY = 96, B_KVB = 104, B_FOLD = 112, B_OFREE = 120, B_XNST = 136, B_GA = 144, B_KVRAW = 152, B_KVRED = 160;
constexpr int OFF_XS = 2 * MLP_STAGE + 16384, OFF_HS = 3 * MLP_STAGE + 16384;
constexpr int OFF_FI = OFF_USTG, OFF_FO = OFF_USTG + 20736, OFF_FW = OFF_USTG + 41472;

__device__ __align__(1024) bf16 g_xn[S_ * D_];
__device__ __align__(1024) bf16 g_h[S_ * D_];
__device__ __align__(1024) bf16 g_u[F_ * D_];
__device__ __align__(1024) bf16 g_o[S_ * D_];
__device__ __align__(1024) bf16 g_wt[1728 * D_];
__device__ __align__(1024) float g_kv[32 * 36 * 20];
__device__ __align__(1024) unsigned g_cnt[32 * 32];
__device__ unsigned g_epoch;
__device__ unsigned g_abort;
constexpr int C_PREP = 1, C_KV = 2, C_U = 4, C_O = 10, C_LN = 26;
#define PROF(i) do {} while (0)
#define PROF1(i) do {} while (0)
#define PROFG(i) do {} while (0)

struct Params {
  CUtensorMap w1, h, w2, u, u_st, xn, wt, wt_st, wqkv_t, o_st, o_ld, wo, x, out;
  const bf16 *xp, *wqkv, *wphi, *b1, *b2;
  uint8_t role[66];
  uint8_t fold[NCTA];
  uint8_t nitems[NATT], na1[NATT];
  uint8_t items[NATT][MAXITEMS];
};

__device__ __forceinline__ uint32_t smem_u32(const void* p) { return (uint32_t)__cvta_generic_to_shared(p); }
__device__ __forceinline__ void mbar_init(uint32_t bar, uint32_t cnt) { asm volatile("mbarrier.init.shared::cta.b64 [%0], %1;" :: "r"(bar), "r"(cnt) : "memory"); }
__device__ __forceinline__ void mbar_expect_tx(uint32_t bar, uint32_t bytes) { asm volatile("mbarrier.arrive.expect_tx.shared::cta.b64 _, [%0], %1;" :: "r"(bar), "r"(bytes) : "memory"); }
__device__ __forceinline__ void mbar_arrive(uint32_t bar) { asm volatile("mbarrier.arrive.shared::cta.b64 _, [%0];" :: "r"(bar) : "memory"); }
__device__ __forceinline__ uint32_t mapa(uint32_t addr, uint32_t rank) { uint32_t r; asm volatile("mapa.shared::cluster.u32 %0, %1, %2;" : "=r"(r) : "r"(addr), "r"(rank)); return r; }
__device__ __forceinline__ void mbar_arrive_remote(uint32_t raddr) { asm volatile("mbarrier.arrive.shared::cluster.b64 _, [%0];" :: "r"(raddr) : "memory"); }
__device__ __forceinline__ bool mbar_test(uint32_t bar, uint32_t parity) {
  uint32_t ok;
  asm volatile("{\n.reg .pred p;\nmbarrier.test_wait.parity.shared::cta.b64 p, [%1], %2;\nselp.u32 %0, 1, 0, p;\n}" : "=r"(ok) : "r"(bar), "r"(parity) : "memory");
  return ok;
}
__device__ __forceinline__ bool mbar_try_wait(uint32_t bar, uint32_t parity) {
  uint32_t ok;
  asm volatile("{\n.reg .pred p;\nmbarrier.try_wait.parity.shared::cta.b64 p, [%1], %2;\nselp.u32 %0, 1, 0, p;\n}" : "=r"(ok) : "r"(bar), "r"(parity) : "memory");
  return ok;
}
__device__ __forceinline__ bool bail(uint32_t& n) {
  if ((++n & 0x3FFu) == 0) {
    if (n >= (1u << 22)) *(volatile unsigned*)&g_abort = 1u;
    if (*(volatile unsigned*)&g_abort) return true;
  }
  return false;
}
__device__ __forceinline__ void mbar_wait(uint32_t bar, uint32_t parity) {
  uint32_t n = 0;
  while (!mbar_try_wait(bar, parity)) { if (bail(n)) break; }
}
__device__ __forceinline__ void tma_2d(uint32_t dst, const CUtensorMap* map, uint32_t bar, int c0, int c1) {
  asm volatile("cp.async.bulk.tensor.2d.shared::cluster.global.mbarrier::complete_tx::bytes [%0], [%1, {%3, %4}], [%2];"
    :: "r"(dst), "l"(map), "r"(bar), "r"(c0), "r"(c1) : "memory");
}
__device__ __forceinline__ void tma_3d(uint32_t dst, const CUtensorMap* map, uint32_t bar, int c0, int c1, int c2) {
  asm volatile("cp.async.bulk.tensor.3d.shared::cluster.global.mbarrier::complete_tx::bytes [%0], [%1, {%3, %4, %5}], [%2];"
    :: "r"(dst), "l"(map), "r"(bar), "r"(c0), "r"(c1), "r"(c2) : "memory");
}
__device__ __forceinline__ void tma_st_2d(const CUtensorMap* map, uint32_t src, int c0, int c1) {
  asm volatile("cp.async.bulk.tensor.2d.global.shared::cta.bulk_group [%0, {%2, %3}], [%1];" :: "l"(map), "r"(src), "r"(c0), "r"(c1) : "memory");
}
__device__ __forceinline__ void tma_st_3d(const CUtensorMap* map, uint32_t src, int c0, int c1, int c2) {
  asm volatile("cp.async.bulk.tensor.3d.global.shared::cta.bulk_group [%0, {%2, %3, %4}], [%1];" :: "l"(map), "r"(src), "r"(c0), "r"(c1), "r"(c2) : "memory");
}
__device__ __forceinline__ void bulk_commit() { asm volatile("cp.async.bulk.commit_group;" ::: "memory"); }
__device__ __forceinline__ void bulk_wait0() { asm volatile("cp.async.bulk.wait_group 0;" ::: "memory"); }
__device__ __forceinline__ void bulk_wait0_read() { asm volatile("cp.async.bulk.wait_group.read 0;" ::: "memory"); }
__device__ __forceinline__ void prefetch_map(const CUtensorMap* map) { asm volatile("prefetch.tensormap [%0];" :: "l"(map) : "memory"); }
__device__ __forceinline__ void fence_async_smem() { asm volatile("fence.proxy.async.shared::cta;" ::: "memory"); }
__device__ __forceinline__ void fence_async_all() { asm volatile("fence.proxy.async;" ::: "memory"); }
__device__ __forceinline__ void wgmma_fence() { asm volatile("wgmma.fence.sync.aligned;" ::: "memory"); }
__device__ __forceinline__ void wgmma_commit() { asm volatile("wgmma.commit_group.sync.aligned;" ::: "memory"); }
template <int N> __device__ __forceinline__ void wgmma_wait() { asm volatile("wgmma.wait_group.sync.aligned %0;" :: "n"(N) : "memory"); }
__device__ __forceinline__ void bar_sync(int id, int n) { asm volatile("bar.sync %0, %1;" :: "r"(id), "r"(n) : "memory"); }
__device__ __forceinline__ void bar_arrive(int id, int n) { asm volatile("bar.arrive %0, %1;" :: "r"(id), "r"(n) : "memory"); }
__device__ __forceinline__ uint64_t make_desc(uint32_t addr, uint32_t lbo, uint32_t sbo, uint32_t swz) {
  return (uint64_t)((addr & 0x3FFFF) >> 4) | ((uint64_t)(lbo >> 4) << 16) | ((uint64_t)(sbo >> 4) << 32) | ((uint64_t)swz << 62);
}
__device__ __forceinline__ void signal(int c) { asm volatile("red.relaxed.gpu.global.add.u32 [%0], 1;" :: "l"(&g_cnt[c * 32]) : "memory"); }
__device__ __forceinline__ void fence_gpu() { asm volatile("fence.acq_rel.gpu;" ::: "memory"); }
__device__ __forceinline__ void wait_cnt(int c, unsigned target) {
  unsigned v; uint32_t n = 0;
  while (true) {
    asm volatile("ld.relaxed.gpu.global.u32 %0, [%1];" : "=r"(v) : "l"(&g_cnt[c * 32]) : "memory");
    if ((int)(v - target) >= 0) break;
    if (bail(n)) break;
  }
}
__device__ __forceinline__ void bulk_st_1d(void* dst, uint32_t src, uint32_t bytes) {
  asm volatile("cp.async.bulk.global.shared::cta.bulk_group [%0], [%1], %2;" :: "l"(dst), "r"(src), "r"(bytes) : "memory");
}
template <int N> __device__ __forceinline__ void bulk_wait() { asm volatile("cp.async.bulk.wait_group %0;" :: "n"(N) : "memory"); }
__device__ __forceinline__ float lds_f32(uint32_t addr) { float v; asm volatile("ld.shared.f32 %0, [%1];" : "=f"(v) : "r"(addr) : "memory"); return v; }
__device__ __forceinline__ uint32_t lds16(uint32_t addr) { unsigned short v; asm volatile("ld.shared.u16 %0, [%1];" : "=h"(v) : "r"(addr) : "memory"); return v; }
__device__ __forceinline__ uint32_t lds32(uint32_t addr) { uint32_t v; asm volatile("ld.shared.b32 %0, [%1];" : "=r"(v) : "r"(addr) : "memory"); return v; }
__device__ __forceinline__ uint32_t pack2(float lo, float hi) { uint32_t r; asm("cvt.rn.bf16x2.f32 %0, %1, %2;" : "=r"(r) : "f"(hi), "f"(lo)); return r; }
__device__ __forceinline__ float bf_lo(uint32_t v) { return __uint_as_float(v << 16); }
__device__ __forceinline__ float bf_hi(uint32_t v) { return __uint_as_float(v & 0xFFFF0000u); }
__device__ __forceinline__ float rbf(float v) { return __bfloat162float(__float2bfloat16_rn(v)); }
__device__ __forceinline__ float ex2(float x) { float r; asm volatile("ex2.approx.ftz.f32 %0, %1;" : "=f"(r) : "f"(x)); return r; }
__device__ __forceinline__ uint32_t opaque(uint32_t x) { uint32_t r; asm volatile("mov.u32 %0, %1;" : "=r"(r) : "r"(x)); return r; }
__device__ __forceinline__ float tanh_fast(float x) { float r; asm("tanh.approx.f32 %0, %1;" : "=f"(r) : "f"(x)); return r; }
__device__ __forceinline__ float rcp_fast(float x) { float r; asm("rcp.approx.ftz.f32 %0, %1;" : "=f"(r) : "f"(x)); return r; }
__device__ __forceinline__ void stsm4(uint32_t addr, uint32_t r0, uint32_t r1, uint32_t r2, uint32_t r3) {
  asm volatile("stmatrix.sync.aligned.m8n8.x4.shared.b16 [%0], {%1, %2, %3, %4};" :: "r"(addr), "r"(r0), "r"(r1), "r"(r2), "r"(r3) : "memory");
}
__device__ __forceinline__ void ldsm4(uint32_t addr, uint32_t& r0, uint32_t& r1, uint32_t& r2, uint32_t& r3) {
  asm volatile("ldmatrix.sync.aligned.m8n8.x4.shared.b16 {%0, %1, %2, %3}, [%4];" : "=r"(r0), "=r"(r1), "=r"(r2), "=r"(r3) : "r"(addr) : "memory");
}
__device__ __forceinline__ void sts128(uint32_t addr, uint32_t a, uint32_t b, uint32_t c, uint32_t d) {
  asm volatile("st.shared.v4.b32 [%0], {%1, %2, %3, %4};" :: "r"(addr), "r"(a), "r"(b), "r"(c), "r"(d) : "memory");
}
__device__ __forceinline__ void sts64(uint32_t addr, uint32_t a, uint32_t b) { asm volatile("st.shared.v2.b32 [%0], {%1, %2};" :: "r"(addr), "r"(a), "r"(b) : "memory"); }
__device__ __forceinline__ void sts32(uint32_t addr, uint32_t a) { asm volatile("st.shared.b32 [%0], %1;" :: "r"(addr), "r"(a) : "memory"); }
__device__ __forceinline__ void mma16816(float (&d)[4], uint32_t a0, uint32_t a1, uint32_t a2, uint32_t a3, uint32_t b0, uint32_t b1) {
  asm volatile("mma.sync.aligned.m16n8k16.row.col.f32.bf16.bf16.f32 {%0, %1, %2, %3}, {%4, %5, %6, %7}, {%8, %9}, {%0, %1, %2, %3};"
    : "+f"(d[0]), "+f"(d[1]), "+f"(d[2]), "+f"(d[3]) : "r"(a0), "r"(a1), "r"(a2), "r"(a3), "r"(b0), "r"(b1));
}
__device__ __forceinline__ uint32_t ldg32(const void* p) { return __ldg(reinterpret_cast<const unsigned*>(p)); }
__device__ __forceinline__ uint32_t ldg16(const void* p) { return __ldg(reinterpret_cast<const unsigned short*>(p)); }

__device__ __forceinline__ void wgmma_ss_n192_t11(float (&d)[96], uint64_t da, uint64_t db, int sc) {
  asm volatile("{\n.reg .pred p;\nsetp.ne.b32 p, %98, 0;\n"
    "wgmma.mma_async.sync.aligned.m64n192k16.f32.bf16.bf16 {%0, %1, %2, %3, %4, %5, %6, %7, %8, %9, %10, %11, %12, %13, %14, %15, %16, %17, %18, %19, %20, %21, %22, %23, %24, %25, %26, %27, %28, %29, %30, %31, %32, %33, %34, %35, %36, %37, %38, %39, %40, %41, %42, %43, %44, %45, %46, %47, %48, %49, %50, %51, %52, %53, %54, %55, %56, %57, %58, %59, %60, %61, %62, %63, %64, %65, %66, %67, %68, %69, %70, %71, %72, %73, %74, %75, %76, %77, %78, %79, %80, %81, %82, %83, %84, %85, %86, %87, %88, %89, %90, %91, %92, %93, %94, %95}, %96, %97, p, 1, 1, 1, 1;\n}\n"
    : "+f"(d[0]), "+f"(d[1]), "+f"(d[2]), "+f"(d[3]), "+f"(d[4]), "+f"(d[5]), "+f"(d[6]), "+f"(d[7]), "+f"(d[8]), "+f"(d[9]), "+f"(d[10]), "+f"(d[11]), "+f"(d[12]), "+f"(d[13]), "+f"(d[14]), "+f"(d[15]), "+f"(d[16]), "+f"(d[17]), "+f"(d[18]), "+f"(d[19]), "+f"(d[20]), "+f"(d[21]), "+f"(d[22]), "+f"(d[23]), "+f"(d[24]), "+f"(d[25]), "+f"(d[26]), "+f"(d[27]), "+f"(d[28]), "+f"(d[29]), "+f"(d[30]), "+f"(d[31]), "+f"(d[32]), "+f"(d[33]), "+f"(d[34]), "+f"(d[35]), "+f"(d[36]), "+f"(d[37]), "+f"(d[38]), "+f"(d[39]), "+f"(d[40]), "+f"(d[41]), "+f"(d[42]), "+f"(d[43]), "+f"(d[44]), "+f"(d[45]), "+f"(d[46]), "+f"(d[47]), "+f"(d[48]), "+f"(d[49]), "+f"(d[50]), "+f"(d[51]), "+f"(d[52]), "+f"(d[53]), "+f"(d[54]), "+f"(d[55]), "+f"(d[56]), "+f"(d[57]), "+f"(d[58]), "+f"(d[59]), "+f"(d[60]), "+f"(d[61]), "+f"(d[62]), "+f"(d[63]), "+f"(d[64]), "+f"(d[65]), "+f"(d[66]), "+f"(d[67]), "+f"(d[68]), "+f"(d[69]), "+f"(d[70]), "+f"(d[71]), "+f"(d[72]), "+f"(d[73]), "+f"(d[74]), "+f"(d[75]), "+f"(d[76]), "+f"(d[77]), "+f"(d[78]), "+f"(d[79]), "+f"(d[80]), "+f"(d[81]), "+f"(d[82]), "+f"(d[83]), "+f"(d[84]), "+f"(d[85]), "+f"(d[86]), "+f"(d[87]), "+f"(d[88]), "+f"(d[89]), "+f"(d[90]), "+f"(d[91]), "+f"(d[92]), "+f"(d[93]), "+f"(d[94]), "+f"(d[95])
    : "l"(da), "l"(db), "r"(sc));
}
__device__ __forceinline__ void wgmma_ss_n96_t01(float (&d)[48], uint64_t da, uint64_t db, int sc) {
  asm volatile("{\n.reg .pred p;\nsetp.ne.b32 p, %50, 0;\n"
    "wgmma.mma_async.sync.aligned.m64n96k16.f32.bf16.bf16 {%0, %1, %2, %3, %4, %5, %6, %7, %8, %9, %10, %11, %12, %13, %14, %15, %16, %17, %18, %19, %20, %21, %22, %23, %24, %25, %26, %27, %28, %29, %30, %31, %32, %33, %34, %35, %36, %37, %38, %39, %40, %41, %42, %43, %44, %45, %46, %47}, %48, %49, p, 1, 1, 0, 1;\n}\n"
    : "+f"(d[0]), "+f"(d[1]), "+f"(d[2]), "+f"(d[3]), "+f"(d[4]), "+f"(d[5]), "+f"(d[6]), "+f"(d[7]), "+f"(d[8]), "+f"(d[9]), "+f"(d[10]), "+f"(d[11]), "+f"(d[12]), "+f"(d[13]), "+f"(d[14]), "+f"(d[15]), "+f"(d[16]), "+f"(d[17]), "+f"(d[18]), "+f"(d[19]), "+f"(d[20]), "+f"(d[21]), "+f"(d[22]), "+f"(d[23]), "+f"(d[24]), "+f"(d[25]), "+f"(d[26]), "+f"(d[27]), "+f"(d[28]), "+f"(d[29]), "+f"(d[30]), "+f"(d[31]), "+f"(d[32]), "+f"(d[33]), "+f"(d[34]), "+f"(d[35]), "+f"(d[36]), "+f"(d[37]), "+f"(d[38]), "+f"(d[39]), "+f"(d[40]), "+f"(d[41]), "+f"(d[42]), "+f"(d[43]), "+f"(d[44]), "+f"(d[45]), "+f"(d[46]), "+f"(d[47])
    : "l"(da), "l"(db), "r"(sc));
}
__device__ __forceinline__ void wgmma_ss_n144_t00(float (&d)[72], uint64_t da, uint64_t db, int sc) {
  asm volatile("{\n.reg .pred p;\nsetp.ne.b32 p, %74, 0;\n"
    "wgmma.mma_async.sync.aligned.m64n144k16.f32.bf16.bf16 {%0, %1, %2, %3, %4, %5, %6, %7, %8, %9, %10, %11, %12, %13, %14, %15, %16, %17, %18, %19, %20, %21, %22, %23, %24, %25, %26, %27, %28, %29, %30, %31, %32, %33, %34, %35, %36, %37, %38, %39, %40, %41, %42, %43, %44, %45, %46, %47, %48, %49, %50, %51, %52, %53, %54, %55, %56, %57, %58, %59, %60, %61, %62, %63, %64, %65, %66, %67, %68, %69, %70, %71}, %72, %73, p, 1, 1, 0, 0;\n}\n"
    : "+f"(d[0]), "+f"(d[1]), "+f"(d[2]), "+f"(d[3]), "+f"(d[4]), "+f"(d[5]), "+f"(d[6]), "+f"(d[7]), "+f"(d[8]), "+f"(d[9]), "+f"(d[10]), "+f"(d[11]), "+f"(d[12]), "+f"(d[13]), "+f"(d[14]), "+f"(d[15]), "+f"(d[16]), "+f"(d[17]), "+f"(d[18]), "+f"(d[19]), "+f"(d[20]), "+f"(d[21]), "+f"(d[22]), "+f"(d[23]), "+f"(d[24]), "+f"(d[25]), "+f"(d[26]), "+f"(d[27]), "+f"(d[28]), "+f"(d[29]), "+f"(d[30]), "+f"(d[31]), "+f"(d[32]), "+f"(d[33]), "+f"(d[34]), "+f"(d[35]), "+f"(d[36]), "+f"(d[37]), "+f"(d[38]), "+f"(d[39]), "+f"(d[40]), "+f"(d[41]), "+f"(d[42]), "+f"(d[43]), "+f"(d[44]), "+f"(d[45]), "+f"(d[46]), "+f"(d[47]), "+f"(d[48]), "+f"(d[49]), "+f"(d[50]), "+f"(d[51]), "+f"(d[52]), "+f"(d[53]), "+f"(d[54]), "+f"(d[55]), "+f"(d[56]), "+f"(d[57]), "+f"(d[58]), "+f"(d[59]), "+f"(d[60]), "+f"(d[61]), "+f"(d[62]), "+f"(d[63]), "+f"(d[64]), "+f"(d[65]), "+f"(d[66]), "+f"(d[67]), "+f"(d[68]), "+f"(d[69]), "+f"(d[70]), "+f"(d[71])
    : "l"(da), "l"(db), "r"(sc));
}
__device__ __forceinline__ void wgmma_ss_n24_t11(float (&d)[12], uint64_t da, uint64_t db, int sc) {
  asm volatile("{\n.reg .pred p;\nsetp.ne.b32 p, %14, 0;\n"
    "wgmma.mma_async.sync.aligned.m64n24k16.f32.bf16.bf16 {%0, %1, %2, %3, %4, %5, %6, %7, %8, %9, %10, %11}, %12, %13, p, 1, 1, 1, 1;\n}\n"
    : "+f"(d[0]), "+f"(d[1]), "+f"(d[2]), "+f"(d[3]), "+f"(d[4]), "+f"(d[5]), "+f"(d[6]), "+f"(d[7]), "+f"(d[8]), "+f"(d[9]), "+f"(d[10]), "+f"(d[11])
    : "l"(da), "l"(db), "r"(sc));
}
__device__ __forceinline__ void wgmma_rs_n80_t0(float (&d)[40], uint32_t a0, uint32_t a1, uint32_t a2, uint32_t a3, uint64_t db, int sc) {
  asm volatile("{\n.reg .pred p;\nsetp.ne.b32 p, %45, 0;\n"
    "wgmma.mma_async.sync.aligned.m64n80k16.f32.bf16.bf16 {%0, %1, %2, %3, %4, %5, %6, %7, %8, %9, %10, %11, %12, %13, %14, %15, %16, %17, %18, %19, %20, %21, %22, %23, %24, %25, %26, %27, %28, %29, %30, %31, %32, %33, %34, %35, %36, %37, %38, %39}, {%40, %41, %42, %43}, %44, p, 1, 1, 0;\n}\n"
    : "+f"(d[0]), "+f"(d[1]), "+f"(d[2]), "+f"(d[3]), "+f"(d[4]), "+f"(d[5]), "+f"(d[6]), "+f"(d[7]), "+f"(d[8]), "+f"(d[9]), "+f"(d[10]), "+f"(d[11]), "+f"(d[12]), "+f"(d[13]), "+f"(d[14]), "+f"(d[15]), "+f"(d[16]), "+f"(d[17]), "+f"(d[18]), "+f"(d[19]), "+f"(d[20]), "+f"(d[21]), "+f"(d[22]), "+f"(d[23]), "+f"(d[24]), "+f"(d[25]), "+f"(d[26]), "+f"(d[27]), "+f"(d[28]), "+f"(d[29]), "+f"(d[30]), "+f"(d[31]), "+f"(d[32]), "+f"(d[33]), "+f"(d[34]), "+f"(d[35]), "+f"(d[36]), "+f"(d[37]), "+f"(d[38]), "+f"(d[39])
    : "r"(a0), "r"(a1), "r"(a2), "r"(a3), "l"(db), "r"(sc));
}

__device__ __forceinline__ float warp_sum(float v) {
#pragma unroll
  for (int o = 16; o > 0; o >>= 1) v += __shfl_xor_sync(0xffffffffu, v, o);
  return v;
}
__device__ __forceinline__ float ln_inv(float var) {
  float sq; asm("sqrt.approx.f32 %0, %1;" : "=f"(sq) : "f"(rbf(rbf(var) + 1e-5f)));
  return rcp_fast(rbf(sq));
}
__device__ __forceinline__ void phase0_ln(const Params& p, uint32_t sbase, int cta, int warp, int lane) {
  uint32_t xl[2][9];
  float xf[2][18];
  const bf16* src = p.xp + (cta * 16 + warp * 2) * D_ + lane * 2;
#pragma unroll
  for (int r = 0; r < 2; r++)
#pragma unroll
    for (int i = 0; i < 9; i++) { xl[r][i] = ldg32(src + r * D_ + i * 64); xf[r][2 * i] = 0.f; xf[r][2 * i + 1] = 0.f; }
  float a1[2] = {1.f, 1.f}, b1[2] = {0.f, 0.f}, a2[2] = {1.f, 1.f}, b2[2] = {0.f, 0.f};
  float s1[2] = {0.f, 0.f}, s2[2] = {0.f, 0.f}, piv[2] = {0.f, 0.f};
  const uint32_t dx = sbase + OFF_XS + warp * 2304 + lane * 4, dh = sbase + OFF_HS + warp * 2304 + lane * 4;
  auto sums = [&](int r, int i0, int i1) {
    if (i0 == 0) { piv[r] = __shfl_sync(0xffffffffu, xf[r][0], 0); s1[r] = 0.f; s2[r] = 0.f; }
    float t0 = 0.f, t1 = 0.f, q0 = 0.f, q1 = 0.f;
#pragma unroll
    for (int i = i0; i < i1; i++) {
      const float a = xf[r][2 * i] - piv[r], b = xf[r][2 * i + 1] - piv[r];
      t0 += a; t1 += b; q0 = fmaf(a, a, q0); q1 = fmaf(b, b, q1);
    }
    s1[r] += t0 + t1; s2[r] += q0 + q1;
  };
  auto norm = [&](int r) {
#pragma unroll
    for (int i = 0; i < 9; i++) {
      sts32(dh + r * 1152 + i * 128, pack2(fmaf(xf[r][2 * i], a2[r], b2[r]), fmaf(xf[r][2 * i + 1], a2[r], b2[r])));
      sts32(dx + r * 1152 + i * 128, pack2(fmaf(xf[r][2 * i], a1[r], b1[r]), fmaf(xf[r][2 * i + 1], a1[r], b1[r])));
    }
  };
#pragma unroll 1
  for (int pass = 0; pass < 2; pass++) {
    switch (pass ? 0 : (cta & 7)) {
      case 0: sums(0, 0, 5); if (!pass) break;
      case 1: sums(0, 5, 9); if (!pass) break;
      case 2: sums(1, 0, 5); if (!pass) break;
      case 3: sums(1, 5, 9); if (!pass) break;
      case 4:
#pragma unroll
        for (int o = 16; o > 0; o >>= 1) {
#pragma unroll
          for (int r = 0; r < 2; r++) { s1[r] += __shfl_xor_sync(0xffffffffu, s1[r], o); s2[r] += __shfl_xor_sync(0xffffffffu, s2[r], o); }
        }
        if (!pass) break;
      case 5:
#pragma unroll
        for (int r = 0; r < 2; r++) {
          const float dm = s1[r] * (1.f / 576.f), mean = piv[r] + dm;
          const float var = fmaxf(fmaf(-dm, dm, s2[r] * (1.f / 576.f)), 0.f);
          const float m = rbf(mean), inv = ln_inv(var);
          const float m2 = rbf((mean - m) * inv), inv2 = ln_inv(var * inv * inv);
          a1[r] = inv; b1[r] = -m * inv;
          a2[r] = inv * inv2; b2[r] = (b1[r] - m2) * inv2;
        }
        if (!pass) break;
      case 6: norm(0); if (!pass) break;
      default: norm(1);
    }
    if (pass == 0) {
      PROF(1);
#pragma unroll
      for (int r = 0; r < 2; r++)
#pragma unroll
        for (int i = 0; i < 9; i++) { xf[r][2 * i] = bf_lo(xl[r][i]); xf[r][2 * i + 1] = bf_hi(xl[r][i]); }
      if (__float_as_uint(xf[0][0]) == 0x7FC12345u && __float_as_uint(xf[1][17]) == 0x7FC54321u) g_abort = 2u;
      bar_arrive(0, 384);
      PROF(61);
    }
  }
  fence_async_smem();
}

__device__ __forceinline__ void phase0(const Params& p, uint32_t sbase, int cta, int warp, int lane) {
  if (cta < 128) {
    phase0_ln(p, sbase, cta, warp, lane);
  } else {
    bar_arrive(0, 384);
    for (int i = (cta - 128) * 256 + warp * 32 + lane; i < 32 * 36 * 5; i += 1024) reinterpret_cast<float4*>(g_kv)[i] = make_float4(0.f, 0.f, 0.f, 0.f);
  }
  bar_arrive(8, 288);
  PROF(2);
  bar_sync(2, 288);
  const bool dry = cta >= 128;
  const int fold = dry ? 32 : p.fold[cta];
  if (fold < 96) {
    const int g = lane >> 2, j = lane & 3;
    const int mat = fold >> 5, jj = warp & 3;
    uint32_t a00[4], a01[2], a10[2], a11;
    if (mat < 2) {
      if (!dry) mbar_wait(sbase + OFF_BAR + B_FOLD, 0);
      const uint32_t W = sbase + OFF_FW + jj * 648;
      const int g2 = 16 + (g & 1);
      const int dd[9] = {2 * j, 2 * j, 2 * j + 8, 2 * j + 8, 16, 16, 2 * j, 2 * j + 8, 16};
      const int ff[9] = {g, g + 8, g, g + 8, g, g + 8, g2, g2, g2};
      uint32_t wr[18];
#pragma unroll
      for (int i = 0; i < 9; i++) { wr[2 * i] = lds16(W + (dd[i] * 18 + ff[i]) * 2); wr[2 * i + 1] = lds16(W + ((dd[i] + 1) * 18 + ff[i]) * 2); }
      auto pk = [&](int i) { return wr[2 * i] | (wr[2 * i + 1] << 16); };
      a00[0] = pk(0); a00[1] = pk(1); a00[2] = pk(2); a00[3] = pk(3);
      a01[0] = j == 0 ? pk(4) : 0u; a01[1] = j == 0 ? pk(5) : 0u;
      a10[0] = g < 2 ? pk(6) : 0u; a10[1] = g < 2 ? pk(7) : 0u;
      a11 = (g < 2 && j == 0) ? pk(8) : 0u;
    } else {
      auto pr = [&](int d, int f) { return (d == f ? 0x3F80u : 0u) | (d + 1 == f ? 0x3F800000u : 0u); };
      a00[0] = pr(2 * j, g); a00[1] = pr(2 * j, g + 8); a00[2] = pr(2 * j + 8, g); a00[3] = pr(2 * j + 8, g + 8);
      a01[0] = 0u; a01[1] = 0u; a10[0] = 0u; a10[1] = 0u;
      a11 = (g < 2 && j == 0) ? pr(16, 16 + g) : 0u;
    }
    if (!dry) mbar_wait(sbase + OFF_BAR + B_FOLD, 0);
    PROF(63);
    const int nb0 = (warp >> 2) * 9;
    const uint32_t src = sbase + OFF_FI + (nb0 * 8 + g) * 144 + jj * 36 + 4 * j;
    const uint32_t dst = sbase + OFF_FO + (8 * (g >> 1) + 2 * jj + (g & 1)) * 288 + nb0 * 16 + 4 * j;
#pragma unroll 3
    for (int nb = 0; nb < 9; nb++) {
      const uint32_t b0 = lds32(src + nb * 1152), b1 = lds32(src + nb * 1152 + 16);
      uint32_t b2 = lds32(src + nb * 1152 + 32 - 4 * j);
      if (j != 0) b2 = 0u;
      float c0[4] = {0.f, 0.f, 0.f, 0.f}, c1[4] = {0.f, 0.f, 0.f, 0.f};
      mma16816(c0, a00[0], a00[1], a00[2], a00[3], b0, b1);
      mma16816(c0, a01[0], a01[1], 0u, 0u, b2, 0u);
      mma16816(c1, a10[0], 0u, a10[1], 0u, b0, b1);
      mma16816(c1, a11, 0u, 0u, 0u, b2, 0u);
      sts32(dst + nb * 16, pack2(c0[0], c0[1]));
      sts32(dst + nb * 16 + 32 * 288, pack2(c0[2], c0[3]));
      if (g < 2) sts32(dst + nb * 16 + 64 * 288, pack2(c1[0], c1[1]));
    }
    fence_async_smem();
    if (!dry) bar_arrive(9, 288);
  }
}

__device__ __forceinline__ void mlp_mainloop(float (&acc)[96], int nkb, int nown, uint32_t rxrdy, int& it, uint32_t sbase, int wg, int t) {
  const uint32_t bars = sbase + OFF_BAR;
  for (int kb = 0; kb < nkb; kb++, it++) {
    const int s = it & 3;
    mbar_wait(bars + B_FULL + 8 * s, (it >> 2) & 1);
    const uint32_t sa = sbase + s * MLP_STAGE + wg * 8192;
    const uint32_t sb = kb < nown ? sbase + OFF_USTG + kb * 24576 : sbase + s * MLP_STAGE + 16384;
    const uint64_t da = make_desc(sa, 8192, 1024, 1), db = make_desc(sb, 8192, 1024, 1);
    wgmma_fence();
#pragma unroll
    for (int kk = 0; kk < 4; kk++) wgmma_ss_n192_t11(acc, da + kk * 128, db + kk * 128, (kb | kk) != 0);
    wgmma_commit();
    if (kb > 0) {
      wgmma_wait<1>();
      if (t == 0) { mbar_arrive(bars + B_EMPTY + 8 * ((it - 1) & 3)); if (kb == 3 && rxrdy) mbar_arrive_remote(rxrdy); }
    }
  }
  wgmma_wait<0>();
  if (t == 0) mbar_arrive(bars + B_EMPTY + 8 * ((it - 1) & 3));
}

__device__ __forceinline__ void g1_epilogue(float (&acc)[96], float hb0, float hb1, uint32_t sbase, int wg, int t) {
  const int lane = t & 31, w4 = t >> 5;
  const uint32_t stg = sbase + OFF_USTG + wg * 24576;
  const int m = lane >> 3, row = w4 * 16 + (m & 1) * 8 + (lane & 7);
  const uint32_t rowaddr = stg + row * 128;
  constexpr float GB = 1.5957691216f;
  float GA = lds_f32(sbase + OFF_BAR + B_GA);
#pragma unroll
  for (int i = 0; i < 24; i += 2) {
    uint32_t r[4];
#pragma unroll
    for (int q = 0; q < 4; q++) {
      const float hb = (q & 1) ? hb1 : hb0;
      const float h0 = fmaf(acc[4 * i + 2 * q], 0.5f, hb), h1 = fmaf(acc[4 * i + 2 * q + 1], 0.5f, hb);
      const float t0 = tanh_fast(h0 * fmaf(h0 * h0, GA, GB)), t1 = tanh_fast(h1 * fmaf(h1 * h1, GA, GB));
      r[q] = pack2(fmaf(h0, t0, h0), fmaf(h1, t1, h1));
    }
    const int blk = i + (m >> 1);
    stsm4(rowaddr + (blk >> 3) * 8192 + (((blk & 7) ^ (row & 7)) << 4), r[0], r[1], r[2], r[3]);
    if ((i & 7) == 6) {
      fence_async_smem();
      bar_arrive(10 + 2 * (i >> 3) + wg, 160);
      if (i < 22) GA = lds_f32(sbase + OFF_BAR + B_GA);
    }
  }
  PROF(16 + wg);
}

__device__ __forceinline__ void sgemm_block(float (&sacc)[48], int it, bool dry, uint32_t sbase, int wg) {
  const int s = it & 3;
  if (!dry) mbar_wait(sbase + OFF_BAR + B_FULL + 8 * s, (it >> 2) & 1);
  const uint32_t sa = sbase + s * MLP_STAGE + wg * 8192, sb = sbase + s * MLP_STAGE + 16384;
  const uint64_t da = make_desc(sa, 16, 1024, 1), db = make_desc(sb, 8192, 1024, 1);
  wgmma_fence();
#pragma unroll
  for (int kk = 0; kk < 4; kk++) wgmma_ss_n96_t01(sacc, da + kk * 2, db + kk * 128, 1);
  wgmma_commit();
}
__device__ __forceinline__ void g2_tail(const Params& p, const float (&acc)[96], int it, uint32_t sbase, int wg, int t, int i_s, int rank, bool dry) {
  const uint32_t bars = sbase + OFF_BAR;
  const int lane = t & 31, w4 = t >> 5, tid = wg * 128 + t;
  const uint32_t xout = sbase + OFF_USTG + tid * 16, xin = xout + 24576;
  const int grow = i_s * 128 + wg * 64 + w4 * 16 + (lane >> 2);
  const float b2a = __bfloat162float(p.b2[grow]), b2b = __bfloat162float(p.b2[grow + 8]);
  float sacc[48], keep[48];
#pragma unroll
  for (int q = 0; q < 6; q++) {
    uint32_t v[4];
#pragma unroll
    for (int e = 0; e < 4; e++) {
      const int a = 8 * q + 2 * e;
      const float lo0 = acc[a], lo1 = acc[a + 1], hi0 = acc[48 + a], hi1 = acc[48 + a + 1];
      v[e] = pack2(rank ? lo0 : hi0, rank ? lo1 : hi1);
      keep[a] = rank ? hi0 : lo0; keep[a + 1] = rank ? hi1 : lo1;
    }
    sts128(xout + q * 4096, v[0], v[1], v[2], v[3]);
  }
  fence_async_smem();
  bar_sync(1, 256);
  if (tid == 0 && !dry) {
    mbar_wait(bars + B_XRDY, 0);
    const uint32_t rin = mapa(sbase + OFF_USTG + 24576, rank ^ 1), rbar = mapa(bars + B_XCH, rank ^ 1);
#pragma unroll
    for (int c = 0; c < 2; c++)
      asm volatile("cp.async.bulk.shared::cluster.shared::cta.mbarrier::complete_tx::bytes [%0], [%1], %2, [%3];"
        :: "r"(rin + c * 12288), "r"(sbase + OFF_USTG + c * 12288), "r"(12288), "r"(rbar + 8 * c) : "memory");
  }
  PROF(30);
#pragma unroll
  for (int i = 0; i < 48; i++) sacc[i] = 0.f;
  int c = dry ? 2 : 0;
#pragma unroll 1
  for (int kb = dry ? 8 : 0; kb < 9 || c < 3; kb++) {
    const bool blk = kb < 9;
    bool chunk = c < 3;
    if (chunk && blk && !dry) {
      const int itk = it + kb;
      chunk = !__all_sync(0xffffffffu, mbar_test(bars + B_FULL + 8 * (itk & 3), (itk >> 2) & 1))
              && __all_sync(0xffffffffu, mbar_test(bars + B_XCH + (c ? 8 : 0), 0));
    }
    if (chunk) {
      if (!dry) mbar_wait(bars + B_XCH + (c ? 8 : 0), 0);
      if (c == 1 && !dry) mbar_wait(bars + B_XCH + 8, 0);
      float g[16];
#pragma unroll
      for (int h = 0; h < 2; h++) {
        uint32_t v[4];
        asm volatile("ld.shared.v4.b32 {%0, %1, %2, %3}, [%4];" : "=r"(v[0]), "=r"(v[1]), "=r"(v[2]), "=r"(v[3]) : "r"(xin + (2 * c + h) * 4096) : "memory");
#pragma unroll
        for (int e = 0; e < 4; e++) {
          const float b = (e & 1) ? b2b : b2a;
          const float y0 = 0.5f * (keep[8 * h + 2 * e] + bf_lo(v[e]) + b), y1 = 0.5f * (keep[8 * h + 2 * e + 1] + bf_hi(v[e]) + b);
          g[8 * h + 2 * e] = fmaf(y0, tanh_fast(y0), y0); g[8 * h + 2 * e + 1] = fmaf(y1, tanh_fast(y1), y1);
        }
      }
#pragma unroll
      for (int i = 0; i < 32; i++) keep[i] = keep[16 + i];
#pragma unroll
      for (int i = 0; i < 16; i++) keep[32 + i] = g[i];
      c++;
      if (blk && !dry) { kb--; continue; }
    }
    if (blk) {
      sgemm_block(sacc, it + kb, dry, sbase, wg);
      PROF(44 + kb);
      if (kb > 0) { wgmma_wait<1>(); if (t == 0 && !dry) mbar_arrive(bars + B_EMPTY + 8 * ((it + kb - 1) & 3)); }
    }
  }
  PROF(20 + wg);
  wgmma_wait<0>();
  PROF(22 + wg);
  it += 9;
  const int s = it & 3;
  if (!dry) mbar_wait(bars + B_FULL + 8 * s, (it >> 2) & 1);
  const uint32_t xs = (dry ? sbase + OFF_USTG : sbase + s * MLP_STAGE) + wg * 12288;
  const int m = lane >> 3, row = w4 * 16 + (m & 1) * 8 + (lane & 7);
#pragma unroll
  for (int i = 0; i < 12; i += 2) {
    const int blk = i + (m >> 1);
    const uint32_t addr = xs + (blk >> 2) * 4096 + row * 64 + (((blk & 3) ^ ((row >> 1) & 3)) << 4);
    uint32_t r[4];
    ldsm4(addr, r[0], r[1], r[2], r[3]);
#pragma unroll
    for (int q = 0; q < 4; q++) {
      const int a = 4 * i + 2 * q;
      r[q] = pack2(fmaf(sacc[a], keep[a], bf_lo(r[q])), fmaf(sacc[a + 1], keep[a + 1], bf_hi(r[q])));
    }
    stsm4(addr, r[0], r[1], r[2], r[3]);
  }
  PROF(29);
  fence_async_smem();
  if (!dry) bar_arrive(6 + wg, 160);
}

__device__ __forceinline__ void att_mainloop(float (&a0)[72], float (&a1)[72], int it0, bool dry, uint32_t sbase, int t) {
  const uint32_t bars = sbase + OFF_BAR;
  for (int kb = dry ? 8 : 0; kb < 9; kb++) {
    const int it = it0 + kb, s = it & 3;
    if (!dry) mbar_wait(bars + B_FULL + 8 * s, (it >> 2) & 1);
    const uint32_t sa = sbase + s * ATT_STAGE, sb = sa + 16384;
    const uint64_t da = make_desc(sa, 16, 1024, 1), db = make_desc(sb, 16, 1024, 1);
    wgmma_fence();
#pragma unroll
    for (int kk = 0; kk < 4; kk++) {
      wgmma_ss_n144_t00(a0, da + kk * 2, db + kk * 2, 1);
      wgmma_ss_n144_t00(a1, da + 512 + kk * 2, db + kk * 2, 1);
    }
    wgmma_commit();
    if (kb > 0) { wgmma_wait<1>(); if (t < 2 && !dry) mbar_arrive(bars + B_EMPTY + 8 * ((it - 1) & 3)); }
  }
}

__device__ __forceinline__ uint32_t max2(uint32_t a, uint32_t b) { uint32_t r; asm("max.bf16x2 %0, %1, %2;" : "=r"(r) : "r"(a), "r"(b)); return r; }
__device__ __forceinline__ uint32_t min2(uint32_t a, uint32_t b) { uint32_t r; asm("min.bf16x2 %0, %1, %2;" : "=r"(r) : "r"(a), "r"(b)); return r; }
__device__ __forceinline__ void softmax18(const uint32_t (&w)[9], uint32_t (&P)[18]) {
  constexpr float L2E = 1.4426950408889634f;
  const uint32_t mxp = max2(max2(max2(max2(w[0], w[1]), max2(w[2], w[3])), max2(max2(w[4], w[5]), max2(w[6], w[7]))), w[8]);
  const uint32_t mnp = min2(min2(min2(min2(w[0], w[1]), min2(w[2], w[3])), min2(min2(w[4], w[5]), min2(w[6], w[7]))), w[8]);
  const float cp = -L2E * fmaxf(bf_lo(mxp), bf_hi(mxp)), cn = L2E * fminf(bf_lo(mnp), bf_hi(mnp));
#pragma unroll
  for (int h = 0; h < 2; h++) {
    const float sc = h ? -L2E : L2E, c = h ? cn : cp;
    float e[18];
#pragma unroll
    for (int i = 0; i < 9; i++) { e[2 * i] = ex2(fmaf(bf_lo(w[i]), sc, c)); e[2 * i + 1] = ex2(fmaf(bf_hi(w[i]), sc, c)); }
    float s3[3] = {e[0], e[1], e[2]};
#pragma unroll
    for (int i = 3; i < 18; i++) s3[i % 3] += e[i];
    const float inv = rcp_fast(s3[0] + s3[1] + s3[2]);
#pragma unroll
    for (int i = 0; i < 9; i++) P[9 * h + i] = pack2(e[2 * i] * inv, e[2 * i + 1] * inv);
  }
}
__device__ __forceinline__ void pack_acc(const float (&a)[72], uint32_t (&k)[36]) {
#pragma unroll
  for (int gp = 0; gp < 2; gp++)
#pragma unroll
    for (int r = 0; r < 2; r++)
#pragma unroll
      for (int i = 0; i < 9; i++) k[gp * 18 + r * 9 + i] = pack2(a[gp * 36 + 4 * i + 2 * r], a[gp * 36 + 4 * i + 2 * r + 1]);
}
__device__ __forceinline__ void a1_epilogue(uint32_t (&k0)[36], uint32_t (&k1)[36], float (&kv0)[12], float (&kv1)[12], float (&kv2)[12], float (&kv3)[12],
                                            int fresh, uint32_t stg, int wg, int t) {
  const int lane = t & 31, w4 = t >> 5, g = lane >> 2, j = lane & 3;
  const uint32_t ph = stg + j * PH_HS + (w4 * 2) * 640 + g * 16, vv = stg + 4 * PH_HS + j * V_HS + (w4 * 2) * 384 + g * 16;
#pragma unroll
  for (int r = 0; r < 2; r++) {
    sts128(vv + r * 384, k0[18 + 9 * r], k0[19 + 9 * r], k0[20 + 9 * r], k0[21 + 9 * r]);
    sts128(vv + r * 384 + 128, k0[22 + 9 * r], k0[23 + 9 * r], k0[24 + 9 * r], k0[25 + 9 * r]);
    sts64(vv + r * 384 + 256, k0[26 + 9 * r], 0x00003F80u);
  }
#pragma unroll 1
  for (int u = 0; u < 4; u++) {
    uint32_t w[9], P[18];
#pragma unroll
    for (int i = 0; i < 9; i++) { w[i] = k0[i]; k0[i] = k0[9 + i]; k0[9 + i] = k1[i]; k1[i] = k1[9 + i]; }
    softmax18(w, P);
    if (u == 2) {
      wgmma_wait<0>();
      bar_sync(4 + wg, 128);
#pragma unroll
      for (int r = 0; r < 2; r++) {
        sts128(vv + r * 384, k1[18 + 9 * r], k1[19 + 9 * r], k1[20 + 9 * r], k1[21 + 9 * r]);
        sts128(vv + r * 384 + 128, k1[22 + 9 * r], k1[23 + 9 * r], k1[24 + 9 * r], k1[25 + 9 * r]);
        sts64(vv + r * 384 + 256, k1[26 + 9 * r], 0x00003F80u);
      }
    }
    const uint32_t pr = ph + (u & 1) * 640;
#pragma unroll
    for (int c = 0; c < 4; c++) sts128(pr + c * 128, P[4 * c], P[4 * c + 1], P[4 * c + 2], P[4 * c + 3]);
    sts64(pr + 512, P[16], P[17]);
    if (u & 1) {
      fence_async_smem();
      bar_sync(4 + wg, 128);
      const uint32_t so = opaque(stg);
      const uint64_t da = make_desc(so, 640, 128, 0), db = make_desc(so + 4 * PH_HS, 384, 128, 0);
      wgmma_fence();
#pragma unroll
      for (int ks = 0; ks < 4; ks++) {
        const int sc = (ks > 0) | (u >> 1) | !fresh;
        wgmma_ss_n24_t11(kv0, da + (0 * PH_HS + ks * 1280) / 16, db + (0 * V_HS + ks * 768) / 16, sc);
        wgmma_ss_n24_t11(kv1, da + (1 * PH_HS + ks * 1280) / 16, db + (1 * V_HS + ks * 768) / 16, sc);
        wgmma_ss_n24_t11(kv2, da + (2 * PH_HS + ks * 1280) / 16, db + (2 * V_HS + ks * 768) / 16, sc);
        wgmma_ss_n24_t11(kv3, da + (3 * PH_HS + ks * 1280) / 16, db + (3 * V_HS + ks * 768) / 16, sc);
      }
      wgmma_commit();
    }
  }
  wgmma_wait<0>();
}
__device__ __forceinline__ void kv_stage(const float (&kv)[12], uint32_t dst, int t) {
  const int lane = t & 31, w4 = t >> 5, g = lane >> 2, j = lane & 3;
#pragma unroll
  for (int r = 0; r < 2; r++) {
    const int f = w4 * 16 + g + 8 * r;
    if (f < 36) {
      const uint32_t a = dst + f * 80 + j * 8;
      sts64(a, __float_as_uint(kv[2 * r]), __float_as_uint(kv[2 * r + 1]));
      sts64(a + 32, __float_as_uint(kv[4 + 2 * r]), __float_as_uint(kv[4 + 2 * r + 1]));
      if (j < 2) sts64(a + 64, __float_as_uint(kv[8 + 2 * r]), j == 0 ? __float_as_uint(kv[8 + 2 * r + 1]) : 0u);
    }
  }
}

template <class Prep>
__device__ __forceinline__ void a2_epilogue(uint32_t (&k0)[36], uint32_t (&k1)[36], uint32_t kvb, uint32_t ostg, uint32_t ofree, int& nst, bool dry,
                                            bool first, Prep prep, int wg, int t, int pk) {
  const int lane = t & 31, w4 = t >> 5, g = lane >> 2, j = lane & 3;
#pragma unroll 1
  for (int q = dry ? 3 : 0; q < 4; q++) {
    uint32_t w0[9], w1[9], P0[18], P1[18];
#pragma unroll
    for (int i = 0; i < 9; i++) { w0[i] = k0[i]; w1[i] = k0[9 + i]; }
#pragma unroll
    for (int i = 0; i < 18; i++) { k0[i] = k0[18 + i]; k0[18 + i] = k1[i]; k1[i] = k1[18 + i]; }
    if (pk >= 0) PROF(pk + 4 * q);
    softmax18(w0, P0);
    softmax18(w1, P1);
    if (pk >= 0) PROF(pk + 4 * q + 1);
    if (first && (q == 0 || dry)) prep();
    const int gp = q & 1;
    float o[40];
    const uint64_t db = make_desc(opaque(kvb) + gp * KVB_BYTES, 1280, 128, 0);
    wgmma_fence();
#pragma unroll
    for (int ks = 0; ks < 9; ks++) wgmma_rs_n80_t0(o, P0[2 * ks], P1[2 * ks], P0[2 * ks + 1], P1[2 * ks + 1], db + ks * 160, ks != 0);
    wgmma_commit();
    wgmma_wait<0>();
    if (pk >= 0) PROF(pk + 4 * q + 2);
    const float i0 = __fdividef(1.f, o[36] + 1e-6f), i1 = __fdividef(1.f, o[38] + 1e-6f);
    if (gp == 0) mbar_wait(ofree, (nst & 1) ^ 1);
    const uint32_t dst = ostg + (w4 * 16 + g) * 288 + gp * 144 + j * 36;
#pragma unroll
    for (int i = 0; i < 9; i++) {
      sts32(dst + 4 * i, pack2(o[4 * i] * i0, o[4 * i + 1] * i0));
      sts32(dst + 8 * 288 + 4 * i, pack2(o[4 * i + 2] * i1, o[4 * i + 3] * i1));
    }
    if (gp == 1 && !dry) { fence_async_smem(); bar_arrive(6 + wg, 160); nst++; }
    if (pk >= 0) PROF(pk + 4 * q + 3);
  }
}
__device__ __forceinline__ void zero_kvb(uint32_t kvb, int t) {
#pragma unroll 5
  for (int c = t; c < 2880; c += 128) sts128(kvb + c * 16, 0u, 0u, 0u, 0u);
}
__device__ __forceinline__ void build_kvb(uint32_t kvb, uint32_t src, int s0, int t) {
  const int n0 = t & 15, jn = (n0 >> 1) & 3, e = n0 & 1;
#pragma unroll 1
  for (int sl = s0 + (t >> 4); sl < 36; sl += 8) {
    const int grp = sl >= 18, r = sl - 18 * grp;
    const uint32_t a = src + ((grp * 4 + jn) * 720 + r * 40) * 4, d = kvb + grp * KVB_BYTES + r * 1280 + n0 * 16 + jn * 4;
    float lo[5], hi[5];
#pragma unroll
    for (int m = 0; m < 5; m++) {
      const int i = (n0 >> 3) + 2 * m, col = (i < 9) ? 2 * i + e : 18;
      lo[m] = lds_f32(a + col * 4); hi[m] = lds_f32(a + col * 4 + 80);
    }
#pragma unroll
    for (int m = 0; m < 5; m++) if (m < 4 || n0 < 8 || e == 0) sts32(d + m * 256, pack2(lo[m], hi[m]));
  }
}

__device__ __forceinline__ void att_item(uint32_t (&k0)[36], uint32_t (&k1)[36], int k, int n, int it_base, bool dry, uint32_t sbase, int wg, int t) {
  float a0[72], a1[72];
#pragma unroll
  for (int i = 0; i < 72; i++) { a0[i] = 0.f; a1[i] = 0.f; }
  if (k > 0 && !dry) bar_sync(2 + wg, 256);
  att_mainloop(a0, a1, it_base + k * 9, dry, sbase, t);
  if (k + 1 < n && !dry) bar_arrive(2 + (wg ^ 1), 256);
  wgmma_wait<0>();
  if (t < 2 && !dry) mbar_arrive(sbase + OFF_BAR + B_EMPTY + 8 * ((it_base + k * 9 + 8) & 3));
  PROF(24 + 2 * k);
  pack_acc(a0, k0);
  pack_acc(a1, k1);
}

__device__ __forceinline__ void att_consumer(const Params& p, int slot, int it_base, unsigned epoch, uint32_t sbase, int wg, int t) {
  const int n = p.nitems[slot], na1 = p.na1[slot];
  const uint32_t bars = sbase + OFF_BAR;
  int nst = 0;
  const int dry_kind = slot < 24 ? 1 + (slot & 1) + (wg == 0 ? 2 : 0) : 0;
#pragma unroll 1
  for (int pass = dry_kind ? 0 : 1; pass < 2; pass++) {
    const bool dry = pass == 0;
    {
      float kv0[12], kv1[12], kv2[12], kv3[12];
      const int k_end = dry ? ((dry_kind & 1) ? wg + 1 : 0) : na1;
#pragma unroll 1
      for (int k = wg; k < k_end; k += 2) {
        uint32_t k0[36], k1[36];
        att_item(k0, k1, k, n, it_base, dry, sbase, wg, t);
        if (dry_kind == 3 && dry) break;
        a1_epilogue(k0, k1, kv0, kv1, kv2, kv3, k < 2, sbase + OFF_ATT + wg * A1_STG, wg, t);
        PROF(25 + 2 * k);
      }
      if (wg < k_end && !(dry && dry_kind == 3)) {
        bar_sync(4 + wg, 128);
        const uint32_t ks = sbase + OFF_ATT + wg * A1_STG;
        kv_stage(kv0, ks, t); kv_stage(kv1, ks + 2880, t); kv_stage(kv2, ks + 2 * 2880, t); kv_stage(kv3, ks + 3 * 2880, t);
        fence_async_smem();
        if (!dry) bar_arrive(6 + wg, 160);
      }
    }
    {
      const int k_beg = dry ? wg : na1 + ((na1 ^ wg) & 1), k_end = dry ? ((dry_kind & 1) ? 0 : wg + 1) : n;
      const uint32_t kvb = sbase + OFF_ATT;
#pragma unroll 1
      for (int k = k_beg; k < k_end; k += 2) {
        uint32_t k0[36], k1[36];
        att_item(k0, k1, k, n, it_base, dry, sbase, wg, t);
        if (dry_kind == 4 && dry) break;
        auto prep = [&]() {
          if (k == na1 || dry) {
            const uint32_t raw = sbase + OFF_OSTG;
            if (!dry) {
              if (na1 > 0) mbar_wait(bars + B_KVRED, 0);
              zero_kvb(kvb, t);
              bar_sync(4 + wg, 128);
              mbar_wait(bars + B_KVRAW, 0);
              PROF(60);
            }
            build_kvb(kvb, raw, dry ? 28 : 0, t);
            fence_async_smem();
            if (!dry) { mbar_arrive(bars + B_KVB); PROF(62); }
          }
          if (!dry) mbar_wait(bars + B_KVB, 0);
        };
        a2_epilogue(k0, k1, kvb, sbase + OFF_OSTG + wg * 18432, bars + B_OFREE + 8 * wg, nst, dry, k < na1 + 2 || dry, prep, wg, t, (!dry && k == na1) ? 44 : -1);
        PROF(25 + 2 * k);
      }
    }
  }
}

__device__ __forceinline__ void att_producer(const Params& p, int slot, int it, uint32_t sbase) {
  const uint32_t bars = sbase + OFF_BAR;
  const int n = p.nitems[slot];
  for (int k = 0; k < n; k++) {
    const int item = p.items[slot][k], type = item >> 7, rb = (item >> 3) & 15, g = item & 7;
    const int wrow = (type ? 1152 : 0) + g * 144;
    for (int kb = 0; kb < 9; kb++, it++) {
      const int s = it & 3;
      const uint32_t full = bars + B_FULL + 8 * s, sa = sbase + s * ATT_STAGE;
      mbar_wait(bars + B_EMPTY + 8 * s, ((it >> 2) & 1) ^ 1);
      mbar_expect_tx(full, 16384 + 18432);
      tma_2d(sa, &p.xn, full, kb * 64, rb * 128);
      tma_2d(sa + 16384, &p.wt, full, kb * 64, wrow);
    }
  }
}

__device__ __forceinline__ void att_helper(const Params& p, int slot, unsigned epoch, uint32_t sbase, int wg, int lane) {
  const uint32_t bars = sbase + OFF_BAR;
  const int n = p.nitems[slot], na1 = p.na1[slot];
  if (wg < na1) {
    bar_sync(6 + wg, 160);
    if (lane == 0) {
      asm volatile("cp.reduce.async.bulk.global.shared::cta.bulk_group.add.f32 [%0], [%1], %2;"
        :: "l"(g_kv + (p.items[slot][0] & 7) * 2880), "r"(sbase + OFF_ATT + wg * A1_STG), "r"(11520) : "memory");
      bulk_commit();
      bulk_wait<0>();
      signal(C_KV);
      mbar_arrive(bars + B_KVRED);
    }
    __syncwarp();
  }
  if (na1 < n && (na1 & 1) == wg && lane == 0) {
    wait_cnt(C_KV, (epoch + 1) * NKV);
    mbar_expect_tx(bars + B_KVRAW, 23040);
    asm volatile("cp.async.bulk.shared::cluster.global.mbarrier::complete_tx::bytes [%0], [%1], %2, [%3];"
      :: "r"(sbase + OFF_OSTG), "l"(g_kv + (p.items[slot][n - 1] & 7) * 5760), "r"(23040), "r"(bars + B_KVRAW) : "memory");
  }
  __syncwarp();
  for (int k = na1 + ((na1 ^ wg) & 1); k < n; k += 2) {
    const int item = p.items[slot][k], rb = (item >> 3) & 15, g = item & 7;
    for (int mb = 0; mb < 2; mb++) {
      bar_sync(6 + wg, 160);
      if (lane == 0) {
        tma_st_2d(&p.o_st, sbase + OFF_OSTG + wg * 18432, g * 144, rb * 128 + mb * 64);
        bulk_commit();
        bulk_wait<0>();
        mbar_arrive(bars + B_OFREE + 8 * wg);
        if (mb == 1) signal(C_O + rb);
      }
      __syncwarp();
    }
  }
}

__global__ void __cluster_dims__(2, 1, 1) __launch_bounds__(384, 1) fused_kernel(const __grid_constant__ Params p) {
  extern __shared__ uint8_t smem_raw[];
  const uint32_t sbase = (smem_u32(smem_raw) + 1023) & ~1023u;
  const uint32_t bars = sbase + OFF_BAR;
  const int wg = threadIdx.x >> 7, t = threadIdx.x & 127;
  const int cta = blockIdx.x, rank = cta & 1;
  PROF(0);
  PROFG(39);
  if (wg == 2) {
    asm volatile("setmaxnreg.dec.sync.aligned.u32 40;");
    bar_sync(0, 384);
    if (threadIdx.x == 256) {
      const int fold = p.fold[cta];
      mbar_init(bars + B_FOLD, 1);
      if (fold < 96) {
        asm volatile("fence.mbarrier_init.release.cluster;" ::: "memory");
        mbar_expect_tx(bars + B_FOLD, 20736 + 2592);
        tma_2d(sbase + OFF_FI, &p.wqkv_t, bars + B_FOLD, (fold >> 5) * D_ + ((fold >> 2) & 7) * 72, (fold & 3) * 144);
        asm volatile("cp.async.bulk.shared::cluster.global.mbarrier::complete_tx::bytes [%0], [%1], %2, [%3];"
          :: "r"(sbase + OFF_FW), "l"(p.wphi + ((fold >> 2) & 7) * 1296), "r"(2592), "r"(bars + B_FOLD) : "memory");
      }
      for (int s = 0; s < 4; s++) { mbar_init(bars + B_FULL + 8 * s, 1); mbar_init(bars + B_EMPTY + 8 * s, 2); mbar_init(bars + B_XCH + 8 * s, 1); }
      mbar_init(bars + B_XRDY, 2);
      mbar_init(bars + B_KVB, 128);
      mbar_init(bars + B_OFREE, 1); mbar_init(bars + B_OFREE + 8, 1);
      mbar_init(bars + B_XNST, 1);
      mbar_init(bars + B_KVRAW, 1);
      mbar_init(bars + B_KVRED, (!(p.role[cta >> 1] < 54)) ? 2 : 1);
      asm volatile("st.shared.f32 [%0], %1;" :: "r"(bars + B_GA), "f"(0.28541926f) : "memory");
      asm volatile("fence.mbarrier_init.release.cluster;" ::: "memory");
      for (int c = 0; c < 2; c++) mbar_expect_tx(bars + B_XCH + 8 * c, 12288);
    }
    __syncwarp();
    asm volatile("barrier.cluster.arrive.relaxed.aligned;" ::: "memory");
    bar_sync(3, 128);
    if (t < 32) bar_arrive(2, 288);
    unsigned epoch;
    asm volatile("ld.relaxed.gpu.global.u32 %0, [%1];" : "=r"(epoch) : "l"(&g_epoch) : "memory");
    const int role = p.role[cta >> 1];
    const bool is_mlp = role < 54;
    const int fi = role / 3, j = role % 3;
    const bool owner = is_mlp && fi < 16;
    const int fold = p.fold[cta];
    const int slot = is_mlp ? (24 + (fi - 16) * 6 + j * 2 + rank) : ((role - 54) * 2 + rank);
    asm volatile("barrier.cluster.wait.acquire.aligned;" ::: "memory");
    const int warp = t >> 5, lane = t & 31;
    if (warp == 0) {
      if (lane == 0) {
        int it = 0;
        if (is_mlp)
          for (int s = 0; s < 4; s++) { mbar_expect_tx(bars + B_FULL + 8 * s, MLP_STAGE); tma_3d(sbase + s * MLP_STAGE, &p.w1, bars + B_FULL + 8 * s, 0, s * 64, (fi + 18 * rank) * 2); }
        if (is_mlp) {
          prefetch_map(&p.h); prefetch_map(&p.w2); prefetch_map(&p.u);
          const int f = fi + 18 * rank;
          PROF1(43);
          wait_cnt(C_LN + ((cta >> 1) & 3), (epoch + 1) * 128);
          PROF1(3);
          if (cta < 128) mbar_wait(bars + B_XNST, 0);
          for (int s = 0; s < 4; s++) tma_3d(sbase + s * MLP_STAGE + 16384, &p.h, bars + B_FULL + 8 * s, 0, s * 64, j * 3);
          for (it = 4; it < 32; it++) {
            const int s = it & 3;
            const uint32_t full = bars + B_FULL + 8 * s, sa = sbase + s * MLP_STAGE;
            mbar_wait(bars + B_EMPTY + 8 * s, ((it >> 2) & 1) ^ 1);
            mbar_expect_tx(full, MLP_STAGE);
            tma_3d(sa, &p.w1, full, 0, it * 64, f * 2);
            tma_3d(sa + 16384, &p.h, full, 0, it * 64, j * 3);
            if (owner && it >= 22 && it < 28 && (it % 3) == j) {
              const int q = it - 22, kb = q < 2 ? 2 * fi + q : ((q - 2 < 2 * fi) ? q - 2 : q);
              asm volatile("cp.async.bulk.prefetch.tensor.3d.L2.global.tile [%0, {%1, %2, %3}];" :: "l"(&p.w2), "r"(0), "r"(rank * 2304 + kb * 64), "r"(fi * 2) : "memory");
            }
          }
          if (owner) {
            const int k0 = rank * 2304;
            for (int q = 0; q < 4; q++) {
              const int s = (it + q) & 3, kb = q < 2 ? 2 * fi + q : (fi == 0 ? q : q - 2);
              mbar_wait(bars + B_EMPTY + 8 * s, (((it + q) >> 2) & 1) ^ 1);
              mbar_expect_tx(bars + B_FULL + 8 * s, q < 2 ? 16384 : MLP_STAGE);
              tma_3d(sbase + s * MLP_STAGE, &p.w2, bars + B_FULL + 8 * s, 0, k0 + kb * 64, fi * 2);
            }
            wait_cnt(C_U + j * 2 + rank, (epoch + 1) * 36);
            PROF1(6);
            for (int q = 2; q < 4; q++) { const int s = (it + q) & 3, kb = fi == 0 ? q : q - 2; tma_3d(sbase + s * MLP_STAGE + 16384, &p.u, bars + B_FULL + 8 * s, 0, k0 + kb * 64, j * 3); }
            it += 4;
            for (int q = 4; q < 36; q++, it++) {
              const int s = it & 3, kb = (q - 2 < 2 * fi) ? q - 2 : q;
              const uint32_t full = bars + B_FULL + 8 * s, sa = sbase + s * MLP_STAGE;
              mbar_wait(bars + B_EMPTY + 8 * s, ((it >> 2) & 1) ^ 1);
              mbar_expect_tx(full, MLP_STAGE);
              tma_3d(sa, &p.w2, full, 0, k0 + kb * 64, fi * 2);
              tma_3d(sa + 16384, &p.u, full, 0, k0 + kb * 64, j * 3);
            }
            wait_cnt(C_O + fi, (epoch + 1) * 4);
            const int c0 = j * 192 + rank * 96;
            for (int kb = 0; kb < 9; kb++, it++) {
              const int s = it & 3;
              const uint32_t full = bars + B_FULL + 8 * s, sa = sbase + s * MLP_STAGE;
              mbar_wait(bars + B_EMPTY + 8 * s, ((it >> 2) & 1) ^ 1);
              mbar_expect_tx(full, 32768);
              tma_2d(sa, &p.o_ld, full, kb * 64, fi * 128);
              tma_2d(sa + 16384, &p.wo, full, c0, kb * 64);
              tma_2d(sa + 16384 + 8192, &p.wo, full, c0 + 64, kb * 64);
            }
            {
              const int s = it & 3;
              const uint32_t full = bars + B_FULL + 8 * s, sa = sbase + s * MLP_STAGE;
              mbar_wait(bars + B_EMPTY + 8 * s, ((it >> 2) & 1) ^ 1);
              mbar_expect_tx(full, 24576);
              tma_3d(sa, &p.x, full, 0, fi * 128, j * 6 + rank * 3);
              tma_3d(sa + 12288, &p.x, full, 0, fi * 128 + 64, j * 6 + rank * 3);
            }
          }
        }
        if (!owner) {
          prefetch_map(&p.xn); prefetch_map(&p.wt);
          wait_cnt(C_PREP, (epoch + 1) * NCTA);
          PROF1(7);
          att_producer(p, slot, it, sbase);
        }
      }
    } else if (warp < 3) {
      const int hw = warp - 1;
      if (hw == 0) {
        if (lane == 0) PROF1(40);
        bar_sync(8, 288);
        if (lane == 0) {
          PROF1(41);
          if (cta < 128) {
            bulk_st_1d(g_h + cta * 16 * D_, sbase + OFF_HS, 18432); bulk_commit();
            bulk_wait<0>();
            PROF1(42);
            signal(C_LN); signal(C_LN + 1); signal(C_LN + 2); signal(C_LN + 3);
            bulk_st_1d(g_xn + cta * 16 * D_, sbase + OFF_XS, 18432); bulk_commit();
            bulk_wait<0>();
            mbar_arrive(bars + B_XNST);
          } else {
            fence_gpu();
          }
        }
        __syncwarp();
        if (fold < 96) {
          bar_sync(9, 288);
          if (lane == 0) {
            const int mat = fold >> 5, gi = (fold >> 2) & 7;
            tma_st_2d(&p.wt_st, sbase + OFF_FO, (fold & 3) * 144, mat == 0 ? 1152 + gi * 72 : gi * 144 + (mat == 2 ? 72 : 0));
            bulk_commit();
            bulk_wait<0>();
          }
        }
        if (lane == 0) signal(C_PREP);
        __syncwarp();
      }
      if (is_mlp) {
        for (int c = 0; c < 3; c++) {
          bar_sync(10 + 2 * c + hw, 160);
          if (lane == 0 && hw == 0) PROF1(44 + c);
          if (lane == 0) { tma_st_2d(&p.u_st, sbase + OFF_USTG + hw * 24576 + c * 8192, j * 192 + c * 64, (fi + 18 * rank) * 128 + hw * 64); bulk_commit(); }
        }
        if (lane == 0) {
          bulk_wait<0>();
          PROF1(18 + hw);
          signal(C_U + j * 2 + rank);
        }
        __syncwarp();
        if (owner) {
          bar_sync(6 + hw, 160);
          if (lane == 0) {
            tma_st_3d(&p.out, sbase + (77 & 3) * MLP_STAGE + hw * 12288, 0, fi * 128 + hw * 64, j * 6 + rank * 3);
            bulk_commit();
            bulk_wait<0>();
            PROF1(14 + hw);
          }
        }
      }
      if (!owner) att_helper(p, slot, epoch, sbase, hw, lane);
      if (cta == 0 && hw == 0 && lane == 0) asm volatile("st.relaxed.gpu.global.u32 [%0], %1;" :: "l"(&g_epoch), "r"(epoch + 1) : "memory");
    }
  } else {
    asm volatile("setmaxnreg.inc.sync.aligned.u32 232;");
    asm volatile("barrier.cluster.arrive.relaxed.aligned;" ::: "memory");
    phase0(p, sbase, cta, threadIdx.x >> 5, threadIdx.x & 31);
    unsigned epoch;
    asm volatile("ld.relaxed.gpu.global.u32 %0, [%1];" : "=r"(epoch) : "l"(&g_epoch) : "memory");
    const int role = p.role[cta >> 1];
    const bool is_mlp = role < 54;
    const int fi = role / 3, j = role % 3;
    const bool owner = is_mlp && fi < 16;
    const int slot = is_mlp ? (24 + (fi - 16) * 6 + j * 2 + rank) : ((role - 54) * 2 + rank);
    asm volatile("barrier.cluster.wait.acquire.aligned;" ::: "memory");
    PROF(4);
    int it = 0;
    if (is_mlp) {
      const int brow = (fi + 18 * rank) * 128 + wg * 64 + (t >> 5) * 16 + ((t & 31) >> 2);
      const float hb0 = 0.5f * __bfloat162float(p.b1[brow]), hb1 = 0.5f * __bfloat162float(p.b1[brow + 8]);
      float acc[96];
#pragma unroll
      for (int i = 0; i < 96; i++) acc[i] = 0.f;
#pragma unroll 1
      for (int pass = cta >= 128 ? 0 : 1; pass < 2; pass++) {
        if (pass == 1) {
          mlp_mainloop(acc, 32, 0, 0u, it, sbase, wg, t);
          PROF(8 + wg);
          g1_epilogue(acc, hb0, hb1, sbase, wg, t);
          bar_sync(1, 256);
          PROF(10 + wg);
          if (owner) mlp_mainloop(acc, 36, 2, mapa(bars + B_XRDY, rank ^ 1), it, sbase, wg, t);
          PROF(12 + wg);
        }
        if (owner || pass == 0) g2_tail(p, acc, it, sbase, wg, t, owner ? fi : 0, rank, pass == 0);
      }
    }
    if (!owner) att_consumer(p, slot, it, epoch, sbase, wg, t);
  }
}

typedef CUresult (*EncodeTiledFn)(CUtensorMap*, CUtensorMapDataType, cuuint32_t, void*, const cuuint64_t*, const cuuint64_t*, const cuuint32_t*,
                                  const cuuint32_t*, CUtensorMapInterleave, CUtensorMapSwizzle, CUtensorMapL2promotion, CUtensorMapFloatOOBfill);

void map2d(EncodeTiledFn enc, CUtensorMap* m, const void* ptr, uint64_t rows, uint64_t cols, uint32_t br, uint32_t bc, CUtensorMapSwizzle sw) {
  cuuint64_t dims[2] = {cols, rows}; cuuint64_t strides[1] = {cols * 2}; cuuint32_t box[2] = {bc, br}; cuuint32_t es[2] = {1, 1};
  enc(m, CU_TENSOR_MAP_DATA_TYPE_BFLOAT16, 2, (void*)ptr, dims, strides, box, es, CU_TENSOR_MAP_INTERLEAVE_NONE, sw,
      CU_TENSOR_MAP_L2_PROMOTION_L2_128B, CU_TENSOR_MAP_FLOAT_OOB_FILL_NONE);
}
void map3d(EncodeTiledFn enc, CUtensorMap* m, const void* ptr, uint64_t rows, uint64_t cols, uint32_t cw, uint32_t br, uint32_t nch, CUtensorMapSwizzle sw) {
  cuuint64_t dims[3] = {cw, rows, cols / cw}; cuuint64_t strides[2] = {cols * 2, (cuuint64_t)cw * 2}; cuuint32_t box[3] = {cw, br, nch}; cuuint32_t es[3] = {1, 1, 1};
  enc(m, CU_TENSOR_MAP_DATA_TYPE_BFLOAT16, 3, (void*)ptr, dims, strides, box, es, CU_TENSOR_MAP_INTERLEAVE_NONE, sw,
      CU_TENSOR_MAP_L2_PROMOTION_L2_128B, CU_TENSOR_MAP_FLOAT_OOB_FILL_NONE);
}

void build_schedule(Params& p) {
  int gpc_clusters[8][9], cnt[8] = {0};
  for (int c = 0; c < 66; c++) {
    int g;
    if (c < 4) g = 0; else if (c < 36) g = (c - 4) % 8; else if (c < 64) g = (c - 36) % 7 + 1; else g = 6 + (c - 64);
    gpc_clusters[g][cnt[g]++] = c;
  }
  int att = 0;
  for (int g = 0; g < 8; g++) {
    int k = 0;
    for (int q = 0; q < 2; q++) for (int j = 0; j < 3; j++) p.role[gpc_clusters[g][k++]] = (uint8_t)((2 * g + q) * 3 + j);
    if (g < 6) { p.role[gpc_clusters[g][k++]] = (uint8_t)(54 + att++); p.role[gpc_clusters[g][k++]] = (uint8_t)(54 + att++); }
    else for (int j = 0; j < 3; j++) p.role[gpc_clusters[g][k++]] = (uint8_t)((16 + (g - 6)) * 3 + j);
  }
  for (int c = 0, nf = 0; c < NCTA; c++) p.fold[c] = (p.role[c >> 1] < 54 && nf < 96) ? (uint8_t)nf++ : (uint8_t)255;
  for (int s = 0; s < NATT; s++) p.nitems[s] = 0;
  auto add = [&](int slot, int type, int rb, int g) { p.items[slot][p.nitems[slot]++] = (uint8_t)((type << 7) | (rb << 3) | g); };
  for (int a = 0; a < 24; a++) for (int r = 0; r < 5; r++) add(a, 0, (a / 8) * 5 + r, a % 8);
  for (int b = 0; b < 8; b++) add(28 + b, 0, 15, b);
  for (int a = 0; a < NATT; a++) p.na1[a] = p.nitems[a];
  int next_rb[4] = {0, 0, 0, 0};
  for (int s = 0; s < 24; s++) for (int r = 0; r < 2; r++) add(s, 1, next_rb[s % 4]++, s % 4);
  for (int s = 24; s < 36; s++) for (int r = 0; r < (s < 28 ? 2 : 1); r++) add(s, 1, next_rb[s % 4]++, s % 4);
}

}

extern "C" void kernel_launch(void* const* d_in, const int* in_sizes, int n_in, void* d_out, int out_size) {
  (void)in_sizes; (void)n_in; (void)out_size;
  static EncodeTiledFn enc = nullptr;
  static void *xn, *h, *u, *o, *wt;
  if (!enc) {
    void* fn = nullptr; cudaDriverEntryPointQueryResult q;
    cudaGetDriverEntryPoint("cuTensorMapEncodeTiled", &fn, cudaEnableDefault, &q);
    enc = (EncodeTiledFn)fn;
    cudaGetSymbolAddress(&xn, g_xn); cudaGetSymbolAddress(&h, g_h); cudaGetSymbolAddress(&u, g_u); cudaGetSymbolAddress(&o, g_o);
    cudaGetSymbolAddress(&wt, g_wt);
    cudaFuncSetAttribute(fused_kernel, cudaFuncAttributeMaxDynamicSharedMemorySize, SMEM_BYTES);
  }
  const bf16* x = (const bf16*)d_in[0];
  const bf16* wqkv = (const bf16*)d_in[1];
  const bf16* wphi = (const bf16*)d_in[2];
  const bf16* wo = (const bf16*)d_in[3];
  const bf16* w1 = (const bf16*)d_in[5];
  const bf16* b1 = (const bf16*)d_in[6];
  const bf16* w2 = (const bf16*)d_in[7];
  const bf16* b2 = (const bf16*)d_in[8];
  Params p;
  const CUtensorMapSwizzle S128 = CU_TENSOR_MAP_SWIZZLE_128B, S64 = CU_TENSOR_MAP_SWIZZLE_64B, S0 = CU_TENSOR_MAP_SWIZZLE_NONE;
  map3d(enc, &p.w1, w1, S_, F_, 64, 64, 2, S128);
  map3d(enc, &p.h, h, S_, D_, 64, 64, 3, S128);
  map3d(enc, &p.w2, w2, F_, S_, 64, 64, 2, S128);
  map3d(enc, &p.u, u, F_, D_, 64, 64, 3, S128);
  map2d(enc, &p.u_st, u, F_, D_, 64, 64, S128);
  map2d(enc, &p.xn, xn, S_, D_, 128, 64, S128);
  map2d(enc, &p.wt, wt, 1728, D_, 144, 64, S128);
  map2d(enc, &p.wt_st, wt, 1728, D_, 72, 144, S0);
  map2d(enc, &p.wqkv_t, wqkv, D_, 3 * D_, 144, 72, S0);
  map2d(enc, &p.o_st, o, S_, D_, 64, 144, S0);
  map2d(enc, &p.o_ld, o, S_, D_, 128, 64, S128);
  map2d(enc, &p.wo, wo, D_, D_, 64, 64, S128);
  map3d(enc, &p.x, x, S_, D_, 32, 64, 3, S64);
  map3d(enc, &p.out, d_out, S_, D_, 32, 64, 3, S64);
  p.xp = x; p.wqkv = wqkv; p.wphi = wphi; p.b1 = b1; p.b2 = b2;
  build_schedule(p);
  fused_kernel<<<NCTA, 384, SMEM_BYTES>>>(p);
}
```
